```python
import torch

def _softmax(x, axis=-1):
    return torch.softmax(x, dim=axis)
def _gelu(x):
    return torch.nn.functional.gelu(x, approximate="tanh")
def _silu(x):
    return torch.nn.functional.silu(x)
def _sigmoid(x):
    return torch.sigmoid(x)
def _layernorm(x, axis=-1, eps=1e-5):
    m = x.mean(dim=axis, keepdim=True)
    v = x.var(dim=axis, keepdim=True, unbiased=False)
    return (x - m) / torch.sqrt(v + eps)
def _scatter_add(tgt, idx, src, axis=0):
    return tgt.clone().index_add_(axis, idx, src)
def _segment_sum(src, seg, n):
    out = torch.zeros((n,) + src.shape[1:], dtype=src.dtype)
    return out.index_add_(0, seg, src)
def _pad(x, pw):
    flat = tuple(v for pair in reversed(pw) for v in pair)
    return torch.nn.functional.pad(x, flat)

kernel_name = 'sequential_preLN__mha_block_cached__dense_activation_relu__decode'

def setup_inputs():

    _w = (lambda a: (lambda t: t.to(torch.bfloat16) if t.is_floating_point() else t)(torch.as_tensor(a)))
    def _A_setup():
        B, Sq, D = 2, 1, 640
        H, Sk, Dh = 32, 16384, 192
        return {
            "x": _w((lambda *s: torch.randn(*s, dtype=torch.bfloat16) * 0.05)(B, Sq, D)),
            "k_cache": _w((lambda *s: torch.randn(*s, dtype=torch.bfloat16) * 3.2)(B, H, Sk, Dh)),
            "v_cache": _w((lambda *s: torch.randn(*s, dtype=torch.bfloat16) * 0.4)(B, H, Sk, Dh)),
            "wq": _w((lambda *s: torch.randn(*s, dtype=torch.bfloat16) * 3.2)(D, H * Dh) * (D ** -0.5)),
            "wo": _w((lambda *s: torch.randn(*s, dtype=torch.bfloat16) * 0.4)(H * Dh, D) * ((H * Dh) ** -0.5)),
        }
    _A_in = _A_setup()

    def _B_setup():
        B, S, D, Dff = 2, 1, 640, 1536
        return {
            "x": _w((lambda *s: torch.randn(*s, dtype=torch.bfloat16) * 0.05)(B, S, D)),
            "w1": _w((lambda *s: torch.randn(*s, dtype=torch.bfloat16) * 0.05)(D, Dff)),
            "w2": _w((lambda *s: torch.randn(*s, dtype=torch.bfloat16) * 0.05)(Dff, D)),
        }
    _B_in = _B_setup()

    return {
        "A_x": _A_in["x"],
        "A_k_cache": _A_in["k_cache"],
        "A_v_cache": _A_in["v_cache"],
        "A_wq": _A_in["wq"],
        "A_wo": _A_in["wo"],
        "B_x": _B_in["x"],
        "B_w1": _B_in["w1"],
        "B_w2": _B_in["w2"],
    }

def reference(A_x, A_k_cache, A_v_cache, A_wq, A_wo, B_x, B_w1, B_w2):
    def _A_ref(x, k_cache, v_cache, wq, wo):
        B, Sq, D = x.shape
        H, Dh = 32, 192
        q = (lambda x, *d: x.permute(*d))((x @ wq).reshape(B, Sq, H, Dh), 0, 2, 1, 3)
        scores = torch.einsum("bhqd,bhkd->bhqk", q, k_cache) * (Dh ** -0.5)
        p = _softmax(scores, axis=-1)
        o = torch.einsum("bhqk,bhkd->bhqd", p, v_cache)
        return (lambda x, *d: x.permute(*d))(o, 0, 2, 1, 3).reshape(B, Sq, H * Dh) @ wo

    def _B_ref(x, w1, w2):
        h = torch.einsum("bsd,df->bsf", x, w1)
        zero = torch.zeros_like(h)
        h = torch.maximum(h, zero)
        return torch.einsum("bsf,fd->bsd", h, w2)

    x = A_x
    h = x + _A_ref(_layernorm(x, axis=-1), A_k_cache, A_v_cache, A_wq, A_wo)
    h2 = h + _B_ref(_layernorm(h, axis=-1), B_w1, B_w2)
    return h2
```

```cpp
#include <cuda_runtime.h>
#include <cuda_bf16.h>
#include <cuda.h>
#include <stdint.h>

namespace fused {

constexpr int NB = 2, DM = 640, NH = 32, SK = 16384, DH = 192, DFF = 1536;
constexpr int TILE = 64;
constexpr int TPB = SK / TILE;
constexpr int NBH = NB * NH;
constexpr int NUNITS = NBH * TPB;
constexpr int TILE_BYTES = TILE * DH * 2;
constexpr int NS = 5;
constexpr int NSX = 9;
constexpr int XCTA = 24;
constexpr int LEAD = 3;
constexpr int MAXG = 132;
constexpr int NROLE = 128;
constexpr int NMLP = 96;
constexpr int NFIN = 80;

constexpr int NDIRECT = 4;
constexpr int YCNT = NROLE * NB - 4 * NDIRECT;

#define MERGE_MARGIN 2
#define W12_AT 0
#define START_DELAY 0
#define USE_EXTRA 1
#define EXP_NOFLUSH 0
#define EXP_NOMERGE 0
#define ZWAIT 600
constexpr int PSLOTS = 8;

constexpr int NCONS_WARPS = 4;
constexpr int NHELP_WARPS = 8;
constexpr int NTHREADS = (NCONS_WARPS + NHELP_WARPS + 1) * 32;

constexpr int OFF_RING = 0;
constexpr int OFF_WQO = OFF_RING + NS * TILE_BYTES;
constexpr int OFF_W1 = OFF_WQO + 61440;
constexpr int OFF_W2 = OFF_W1 + 20480;
constexpr int OFF_MISC = OFF_W2 + 20480;
constexpr int OFF_QRAW = OFF_MISC;
constexpr int OFF_DONE = OFF_QRAW + 2048;
constexpr int OFF_HROW = OFF_DONE + 64;
constexpr int OFF_RED1 = OFF_HROW + 2560;
constexpr int OFF_SBUF = OFF_RED1 + 1024;
constexpr int OFF_STATS = OFF_SBUF + 512;
constexpr int OFF_FRED = OFF_STATS + 128;
constexpr int OFF_OBF = OFF_FRED + 256;
constexpr int OFF_META = OFF_OBF + 128;
constexpr int OFF_EPOCH = OFF_META + 48;
constexpr int OFF_BARS = OFF_EPOCH + 16;
constexpr int NBARS = 2 * NSX + 3;
constexpr int SMEM_BYTES = OFF_BARS + NBARS * 8 + 8;
constexpr int OFF_RED_Q = OFF_W2;
static_assert(SMEM_BYTES <= 232448, "smem");

constexpr float SM_SCALE_LOG2 = 0.07216878364870322f * 1.4426950408889634f;
constexpr float LN_EPS = 1e-5f;

struct __align__(128) Counter64 { unsigned long long v; unsigned long long pad[15]; };
struct __align__(128) Counter32 { unsigned v; unsigned pad[31]; };
__device__ Counter64 g_claim;
__device__ Counter32 g_ycnt;
__device__ Counter32 g_epoch;
__device__ __align__(128) uint4 g_qll[NBH * 32];
__device__ __align__(128) uint4 g_hdr[PSLOTS * MAXG];
__device__ __align__(128) uint4 g_done[NBH];
__device__ __align__(128) uint4 g_dat[PSLOTS * 4 * 8 * MAXG];
__device__ __align__(128) float g_hacc[2][NB * DM];
__device__ __align__(128) uint4 g_y[NDIRECT * 4 * 256];
__device__ __align__(128) uint4 g_z[NMLP * DM];

#define TPDECL(n) do { } while (0)
#define TP(i) do { } while (0)
#define TPOUT(slot, i) do { } while (0)
#define PROF(slot) do { } while (0)
#define PROF_REF() do { } while (0)
#define PROF_REF2() do { } while (0)

__device__ __forceinline__ uint32_t smem_u32(const void* p) { return (uint32_t)__cvta_generic_to_shared(p); }
__device__ __forceinline__ void mbar_init(uint32_t bar, uint32_t cnt) {
    asm volatile("mbarrier.init.shared::cta.b64 [%0], %1;" :: "r"(bar), "r"(cnt) : "memory");
}
__device__ __forceinline__ void mbar_expect_tx(uint32_t bar, uint32_t bytes) {
    asm volatile("mbarrier.arrive.expect_tx.shared::cta.b64 _, [%0], %1;" :: "r"(bar), "r"(bytes) : "memory");
}
__device__ __forceinline__ void mbar_arrive(uint32_t bar) {
    asm volatile("mbarrier.arrive.shared::cta.b64 _, [%0];" :: "r"(bar) : "memory");
}
__device__ __forceinline__ bool mbar_try(uint32_t bar, uint32_t parity) {
    uint32_t ok;
    asm volatile("{\n.reg .pred p;\nmbarrier.try_wait.parity.shared::cta.b64 p, [%1], %2;\nselp.u32 %0, 1, 0, p;\n}"
                 : "=r"(ok) : "r"(bar), "r"(parity) : "memory");
    return ok != 0;
}
constexpr long long SPIN_LIMIT = 4000000000LL;
__device__ __forceinline__ void spin_check(long long t0) { if (clock64() - t0 > SPIN_LIMIT) __trap(); }
__device__ __forceinline__ void mbar_wait(uint32_t bar, uint32_t parity) {
    if (mbar_try(bar, parity)) return;
    const long long t0 = clock64();
    while (!mbar_try(bar, parity)) spin_check(t0);
}
__device__ __forceinline__ void tma2d(uint32_t dst, const CUtensorMap* tm, int c0, int c1, uint32_t bar) {
    asm volatile("cp.async.bulk.tensor.2d.shared::cluster.global.mbarrier::complete_tx::bytes [%0], [%1, {%3, %4}], [%2];"
                 :: "r"(dst), "l"(tm), "r"(bar), "r"(c0), "r"(c1) : "memory");
}
__device__ __forceinline__ void tma2d_hint(uint32_t dst, const CUtensorMap* tm, int c0, int c1, uint32_t bar, uint64_t pol) {
    asm volatile("cp.async.bulk.tensor.2d.shared::cluster.global.mbarrier::complete_tx::bytes.L2::cache_hint [%0], [%1, {%3, %4}], [%2], %5;"
                 :: "r"(dst), "l"(tm), "r"(bar), "r"(c0), "r"(c1), "l"(pol) : "memory");
}
__device__ __forceinline__ void bulk_g2s(uint32_t dst, const void* src, uint32_t bytes, uint32_t bar) {
    asm volatile("cp.async.bulk.shared::cluster.global.mbarrier::complete_tx::bytes [%0], [%1], %2, [%3];"
                 :: "r"(dst), "l"(src), "r"(bytes), "r"(bar) : "memory");
}
__device__ __forceinline__ void named_bar(int id, int nthreads) {
    asm volatile("bar.sync %0, %1;" :: "r"(id), "r"(nthreads) : "memory");
}
__device__ __forceinline__ void ldsm4(uint32_t (&r)[4], uint32_t addr) {
    asm volatile("ldmatrix.sync.aligned.m8n8.x4.shared.b16 {%0,%1,%2,%3}, [%4];"
                 : "=r"(r[0]), "=r"(r[1]), "=r"(r[2]), "=r"(r[3]) : "r"(addr) : "memory");
}
__device__ __forceinline__ void ldsm4t(uint32_t (&r)[4], uint32_t addr) {
    asm volatile("ldmatrix.sync.aligned.m8n8.x4.trans.shared.b16 {%0,%1,%2,%3}, [%4];"
                 : "=r"(r[0]), "=r"(r[1]), "=r"(r[2]), "=r"(r[3]) : "r"(addr) : "memory");
}
__device__ __forceinline__ void mma16816(float (&c)[4], const uint32_t (&a)[4], uint32_t b0, uint32_t b1) {
    asm volatile("mma.sync.aligned.m16n8k16.row.col.f32.bf16.bf16.f32 {%0,%1,%2,%3}, {%4,%5,%6,%7}, {%8,%9}, {%0,%1,%2,%3};"
                 : "+f"(c[0]), "+f"(c[1]), "+f"(c[2]), "+f"(c[3])
                 : "r"(a[0]), "r"(a[1]), "r"(a[2]), "r"(a[3]), "r"(b0), "r"(b1));
}
__device__ __forceinline__ uint32_t pack_bf16(float lo, float hi) {
    uint32_t r;
    asm("cvt.rn.bf16x2.f32 %0, %1, %2;" : "=r"(r) : "f"(hi), "f"(lo));
    return r;
}
__device__ __forceinline__ float ex2(float x) { float y; asm("ex2.approx.ftz.f32 %0, %1;" : "=f"(y) : "f"(x)); return y; }
__device__ __forceinline__ void st_ll(uint4* p, uint32_t a, uint32_t b, uint32_t c, uint32_t d) {
    unsigned long long lo = (unsigned long long)a | ((unsigned long long)b << 32);
    unsigned long long hi = (unsigned long long)c | ((unsigned long long)d << 32);
    asm volatile("{\n.reg .b128 t;\nmov.b128 t, {%1, %2};\nst.relaxed.gpu.global.b128 [%0], t;\n}" :: "l"(p), "l"(lo), "l"(hi) : "memory");
}
__device__ __forceinline__ uint4 ld_ll(const uint4* p) {
    unsigned long long lo, hi;
    asm volatile("{\n.reg .b128 t;\nld.relaxed.gpu.global.b128 t, [%2];\nmov.b128 {%0, %1}, t;\n}" : "=l"(lo), "=l"(hi) : "l"(p) : "memory");
    uint4 r; r.x = (uint32_t)lo; r.y = (uint32_t)(lo >> 32); r.z = (uint32_t)hi; r.w = (uint32_t)(hi >> 32);
    return r;
}
__device__ __forceinline__ unsigned ld_relaxed_u32(const unsigned* p) {
    unsigned v; asm volatile("ld.relaxed.gpu.global.u32 %0, [%1];" : "=r"(v) : "l"(p) : "memory"); return v;
}
__device__ __forceinline__ unsigned long long ld_relaxed_u64(const unsigned long long* p) {
    unsigned long long v; asm volatile("ld.relaxed.gpu.global.u64 %0, [%1];" : "=l"(v) : "l"(p) : "memory"); return v;
}
__device__ __forceinline__ float ld_relaxed_f32(const float* p) {
    float v; asm volatile("ld.relaxed.gpu.global.f32 %0, [%1];" : "=f"(v) : "l"(p) : "memory"); return v;
}
__device__ __forceinline__ void fence_gpu() { asm volatile("fence.acq_rel.gpu;" ::: "memory"); }
__device__ __forceinline__ void red_add_u32(unsigned* p, unsigned v) {
    asm volatile("red.relaxed.gpu.global.add.u32 [%0], %1;" :: "l"(p), "r"(v) : "memory");
}
__device__ __forceinline__ void red_add_f32(float* p, float v) {
    asm volatile("red.relaxed.gpu.global.add.f32 [%0], %1;" :: "l"(p), "f"(v) : "memory");
}
__device__ __forceinline__ void wait_counter(const unsigned* p, unsigned target, unsigned sleep_ns) {
    const long long t0 = clock64();
    while (true) {
        unsigned v;
        asm volatile("ld.acquire.gpu.global.u32 %0, [%1];" : "=r"(v) : "l"(p) : "memory");
        if ((int)(v - target) >= 0) break;
        __nanosleep(sleep_ns); spin_check(t0);
    }
}
__device__ __forceinline__ void cp_async16(uint32_t dst, const void* src) {
    asm volatile("cp.async.cg.shared.global [%0], [%1], 16;" :: "r"(dst), "l"(src) : "memory");
}
__device__ __forceinline__ void cp_async_wait_all() { asm volatile("cp.async.wait_all;" ::: "memory"); }
__device__ __forceinline__ uint4 lds128(uint32_t addr) {
    uint4 r;
    asm volatile("ld.shared.v4.u32 {%0,%1,%2,%3}, [%4];" : "=r"(r.x), "=r"(r.y), "=r"(r.z), "=r"(r.w) : "r"(addr) : "memory");
    return r;
}
__device__ __forceinline__ float warp_max(float v) {
    int i = __float_as_int(v);
    i ^= (i >> 31) & 0x7fffffff;
    i = __reduce_max_sync(0xffffffffu, i);
    i ^= (i >> 31) & 0x7fffffff;
    return __int_as_float(i);
}

__device__ __forceinline__ void ln_row(const float (&v)[3], float* hrow, float2* stats, int hw, int lane, uint32_t (&fr)[5][2]) {
    const int g = lane >> 2, j = lane & 3;
    const bool full = j < 3;
    float* hp = hrow + 80 * hw + g;
    __syncwarp();
    {
        const int i0 = 3 * j;
        hp[16 * (i0 >> 1) + 8 * (i0 & 1)] = v[0];
        if (full) {
            hp[16 * ((i0 + 1) >> 1) + 8 * ((i0 + 1) & 1)] = v[1];
            hp[16 * ((i0 + 2) >> 1) + 8 * ((i0 + 2) & 1)] = v[2];
        }
    }
    const float c = __shfl_sync(0xffffffffu, v[0], 0);
    const float d0 = v[0] - c, d1 = full ? v[1] - c : 0.f, d2 = full ? v[2] - c : 0.f;
    float s1 = d0 + d1 + d2, s2 = d0 * d0 + d1 * d1 + d2 * d2;
#pragma unroll
    for (int o = 16; o >= 1; o >>= 1) { s1 += __shfl_xor_sync(0xffffffffu, s1, o); s2 += __shfl_xor_sync(0xffffffffu, s2, o); }
    if (lane == 0) stats[hw] = make_float2(c + s1 * (1.0f / 80.0f), s2 - s1 * s1 * (1.0f / 80.0f));
    named_bar(2, NHELP_WARPS * 32);
    const float4* sp = reinterpret_cast<const float4*>(stats);
    const float4 a = sp[0], b = sp[1], cc = sp[2], d = sp[3];
    const float mean = (((a.x + a.z) + (b.x + b.z)) + ((cc.x + cc.z) + (d.x + d.z))) * 0.125f;
    const float e0 = a.x - mean, e1 = a.z - mean, e2 = b.x - mean, e3 = b.z - mean, e4 = cc.x - mean, e5 = cc.z - mean, e6 = d.x - mean, e7 = d.z - mean;
    const float m2 = (((a.y + a.w) + (b.y + b.w)) + ((cc.y + cc.w) + (d.y + d.w))) +
                     80.0f * (((e0 * e0 + e1 * e1) + (e2 * e2 + e3 * e3)) + ((e4 * e4 + e5 * e5) + (e6 * e6 + e7 * e7)));
    const float rstd = rsqrtf(fmaxf(m2, 0.f) * (1.0f / DM) + LN_EPS);
    const float* fp = hrow + 80 * hw + 2 * j;
#pragma unroll
    for (int i = 0; i < 5; i++) {
        const float2 p = *reinterpret_cast<const float2*>(fp + 16 * i);
        const float2 q = *reinterpret_cast<const float2*>(fp + 16 * i + 8);
        fr[i][0] = pack_bf16((p.x - mean) * rstd, (p.y - mean) * rstd);
        fr[i][1] = pack_bf16((q.x - mean) * rstd, (q.y - mean) * rstd);
    }
}

__device__ __forceinline__ void ln_rows2(const float (&v)[2][3], float* hrow2, float4* stats, int hw, int lane, uint32_t (&fr)[5][2]) {
    const int g = lane >> 2, j = lane & 3;
    const bool full = j < 3;
    float* hp = hrow2 + 80 * hw + 24 * j + g;
    hp[0] = v[0][0]; hp[DM] = v[1][0];
    if (full) { hp[8] = v[0][1]; hp[16] = v[0][2]; hp[DM + 8] = v[1][1]; hp[DM + 16] = v[1][2]; }
    float c[2], s1[2], s2[2];
#pragma unroll
    for (int r = 0; r < 2; r++) {
        c[r] = __shfl_sync(0xffffffffu, v[r][0], 0);
        const float d0 = v[r][0] - c[r], d1 = full ? v[r][1] - c[r] : 0.f, d2 = full ? v[r][2] - c[r] : 0.f;
        s1[r] = d0 + d1 + d2; s2[r] = d0 * d0 + d1 * d1 + d2 * d2;
    }
#pragma unroll
    for (int o = 16; o >= 1; o >>= 1) {
#pragma unroll
        for (int r = 0; r < 2; r++) { s1[r] += __shfl_xor_sync(0xffffffffu, s1[r], o); s2[r] += __shfl_xor_sync(0xffffffffu, s2[r], o); }
    }
    if (lane == 0) stats[hw] = make_float4(c[0] + s1[0] * (1.0f / 80.0f), s2[0] - s1[0] * s1[0] * (1.0f / 80.0f),
                                           c[1] + s1[1] * (1.0f / 80.0f), s2[1] - s1[1] * s1[1] * (1.0f / 80.0f));
    named_bar(2, NHELP_WARPS * 32);
    const int row = g & 1;
    const float2* sp = reinterpret_cast<const float2*>(stats) + row;
    float mw[8], m2 = 0.f, mean = 0.f;
#pragma unroll
    for (int k = 0; k < 8; k++) { const float2 t = sp[2 * k]; mw[k] = t.x; mean += t.x; m2 += t.y; }
    mean *= 0.125f;
    float dev = 0.f;
#pragma unroll
    for (int k = 0; k < 8; k++) dev += (mw[k] - mean) * (mw[k] - mean);
    const float rstd = rsqrtf(fmaxf(m2 + 80.0f * dev, 0.f) * (1.0f / DM) + LN_EPS);
    const float* fp = hrow2 + row * DM + 80 * hw + 2 * j;
#pragma unroll
    for (int i = 0; i < 5; i++) {
        const float2 p = *reinterpret_cast<const float2*>(fp + 16 * i);
        const float2 q = *reinterpret_cast<const float2*>(fp + 16 * i + 8);
        fr[i][0] = (g < 2) ? pack_bf16((p.x - mean) * rstd, (p.y - mean) * rstd) : 0u;
        fr[i][1] = (g < 2) ? pack_bf16((q.x - mean) * rstd, (q.y - mean) * rstd) : 0u;
    }
}

__global__ void __launch_bounds__(NTHREADS, 1)
fused_decode_kernel(const __grid_constant__ CUtensorMap tmK, const __grid_constant__ CUtensorMap tmV,
                    const __grid_constant__ CUtensorMap tmWo,
                    const __grid_constant__ CUtensorMap tmW1, const __grid_constant__ CUtensorMap tmW2,
                    const __nv_bfloat16* __restrict__ x, const __nv_bfloat16* __restrict__ wq, __nv_bfloat16* __restrict__ out)
{
    extern __shared__ __align__(1024) unsigned char smem[];
    const uint32_t sbase = smem_u32(smem);
    const int tid = threadIdx.x, warp = tid >> 5, lane = tid & 31;
    const int cta = blockIdx.x, G = gridDim.x;

    const uint32_t bar_full = sbase + OFF_BARS;
    const uint32_t bar_empty = bar_full + NSX * 8;
    const uint32_t bar_wo = bar_empty + NSX * 8;
    const int lim0 = (USE_EXTRA && cta >= XCTA) ? NSX : NS;
    const uint32_t bar_w1 = bar_wo + 8;
    const uint32_t bar_w2 = bar_w1 + 8;
    volatile int* meta = reinterpret_cast<volatile int*>(smem + OFF_META);

    uint64_t pol = 0;
    const int ht = tid - NCONS_WARPS * 32;
    auto load_wq = [&]() {
        const __nv_bfloat16* src = wq + cta * 48;
#pragma unroll
        for (int i = 0; i < 15; i++) {
            const int idx = ht + 256 * i, row = idx / 6, u = idx - 6 * row;
            cp_async16(sbase + OFF_WQO + idx * 16, src + (size_t)row * (NH * DH) + u * 8);
        }
        asm volatile("cp.async.commit_group;" ::: "memory");
    };
    if (warp >= NCONS_WARPS && warp < NCONS_WARPS + NHELP_WARPS && cta < NROLE) {
        if (ht < 160) cp_async16(sbase + OFF_HROW + ht * 16, x + ht * 8);
        if (ht == 160) cp_async16(sbase + OFF_EPOCH, &g_epoch);
        asm volatile("cp.async.commit_group;" ::: "memory");
        if (cta < 4 * LEAD) load_wq();
    }
    if (warp == NCONS_WARPS + NHELP_WARPS && lane == 0) {
        PROF(0);
        for (int i = 0; i < NSX; i++) { mbar_init(bar_full + 8 * i, 1); mbar_init(bar_empty + 8 * i, NCONS_WARPS); }
        mbar_init(bar_wo, 1); mbar_init(bar_w1, 1); mbar_init(bar_w2, 1);
        asm volatile("fence.mbarrier_init.release.cluster;" ::: "memory");
        asm volatile("fence.proxy.async.shared::cta;" ::: "memory");
        asm volatile("createpolicy.fractional.L2::evict_first.b64 %0, 1.0;" : "=l"(pol));
        if (START_DELAY > 0) { const long long t0 = clock64(); while (clock64() - t0 < START_DELAY) { } }
        meta[0] = cta;
        mbar_expect_tx(bar_full, TILE_BYTES);
        tma2d_hint(sbase + OFF_RING, &tmK, 0, cta * 192, bar_full, pol);
        mbar_expect_tx(bar_full + 8, TILE_BYTES);
        tma2d_hint(sbase + OFF_RING + TILE_BYTES, &tmV, 0, cta * 192, bar_full + 8, pol);
    }
    __syncthreads();

    if (warp == NCONS_WARPS + NHELP_WARPS) {
        asm volatile("setmaxnreg.dec.sync.aligned.u32 40;");
        if (lane == 0) {
            unsigned long long old = atomicAdd(&g_claim.v, 1ULL);
            PROF_REF();
            int slot = 2, lim = lim0; uint32_t ph = 1;
            int wslot = 0, wlim = lim0; uint32_t wph = 0;
            while (true) {
                const int unit = (int)(old & (NUNITS - 1)) + G;
                if (unit >= NUNITS) break;
                mbar_wait(bar_full + 8 * wslot, wph); if (++wslot == wlim) { wslot = 0; wph ^= 1; wlim = NS; }
                mbar_wait(bar_empty + 8 * slot, ph);
                meta[slot] = unit;
                mbar_expect_tx(bar_full + 8 * slot, TILE_BYTES);
                tma2d_hint(sbase + OFF_RING + slot * TILE_BYTES, &tmK, 0, unit * 192, bar_full + 8 * slot, pol);
                if (++slot == lim) { slot = 0; ph ^= 1; lim = NS; }
                mbar_wait(bar_full + 8 * wslot, wph); if (++wslot == wlim) { wslot = 0; wph ^= 1; wlim = NS; }
                mbar_wait(bar_empty + 8 * slot, ph);
                mbar_expect_tx(bar_full + 8 * slot, TILE_BYTES);
                tma2d_hint(sbase + OFF_RING + slot * TILE_BYTES, &tmV, 0, unit * 192, bar_full + 8 * slot, pol);
                if (++slot == lim) { slot = 0; ph ^= 1; lim = NS; }
                old = atomicAdd(&g_claim.v, 1ULL);
            }
            PROF(2);
            PROF_REF2();
            mbar_wait(bar_empty + 8 * slot, ph);
            meta[slot] = -1;
            mbar_arrive(bar_full + 8 * slot);
            if (lim == NSX) {
                for (int s2 = max(slot, NS); s2 < NSX; s2++)
                    for (int k = 0; k < NCONS_WARPS; k++) mbar_arrive(bar_empty + 8 * s2);
            }
        }
    } else if (warp < NCONS_WARPS) {
        asm volatile("setmaxnreg.dec.sync.aligned.u32 96;");
        const int w = warp, g = lane >> 2, j = lane & 3;
        uint4* const dat_base = g_dat + ((size_t)w * 8 + g) * MAXG + cta;
        uint4* const hdr_base = g_hdr + cta;
        const uint32_t epoch = ld_relaxed_u32(&g_epoch.v);
        const uint32_t flag = epoch + 1u;
        uint32_t koff[3];
        {
            const int key = 16 * w + (lane & 7) + 8 * ((lane >> 3) & 1), hi = lane >> 4;
#pragma unroll
            for (int c = 0; c < 3; c++) { const int r = key * 3 + c; koff[c] = r * 128 + (((r & 7) ^ hi) << 4); }
        }
        uint32_t voff[3];
        {
            const int key = (lane & 7) + 8 * (lane >> 4), hi = (lane >> 3) & 1;
#pragma unroll
            for (int mt = 0; mt < 3; mt++) {
                const int U = 6 * w + 2 * mt + hi, c = U >> 3, u = U & 7, r = key * 3 + c;
                voff[mt] = r * 128 + ((u ^ (r & 7)) << 4);
            }
        }
        const bool act = (g >> 1) == j;
        const uint32_t sel0 = act ? ((g & 1) ? 0x1044u : 0x4410u) : 0x4444u;
        const uint32_t sel1 = act ? ((g & 1) ? 0x3244u : 0x4432u) : 0x4444u;
        float* sbuf = reinterpret_cast<float*>(smem + OFF_SBUF);
        const uint32_t qraw = sbase + OFF_QRAW + w * 512;

        uint32_t qf[24];
        float o[3][4];
        float m_run = -INFINITY, l_run = 0.f;
        int cur_bh = -1, pre_bh = -1, done_bh = -1, par = 0;
        const uint32_t dnraw = sbase + OFF_DONE + w * 16;
        int slot = 0, lim = lim0; uint32_t ph = 0;

        auto advance_to = [&](int nb) {
#pragma unroll 1
            while (cur_bh < nb) {
                if (cur_bh >= 0 && !EXP_NOFLUSH) {
                    if (cur_bh >= PSLOTS && !EXP_NOMERGE) {
                        uint4 dn = lds128(dnraw);
                        if (done_bh != cur_bh - PSLOTS || dn.x != flag || dn.y != flag || dn.z != flag || dn.w != flag) {
                            const long long t0 = clock64();
                            do { dn = ld_ll(g_done + cur_bh - PSLOTS); spin_check(t0); } while (dn.x != flag || dn.y != flag || dn.z != flag || dn.w != flag);
                        }
                    }
                    const uint32_t tag = flag * 8u + (uint32_t)(cur_bh >> 3);
                    float lo[3], hi[3];
#pragma unroll
                    for (int mt = 0; mt < 3; mt++) {
                        lo[mt] = o[mt][0] + o[mt][1]; hi[mt] = o[mt][2] + o[mt][3];
                        lo[mt] += __shfl_xor_sync(0xffffffffu, lo[mt], 1); hi[mt] += __shfl_xor_sync(0xffffffffu, hi[mt], 1);
                        lo[mt] += __shfl_xor_sync(0xffffffffu, lo[mt], 2); hi[mt] += __shfl_xor_sync(0xffffffffu, hi[mt], 2);
                    }
                    if (j == 0)
                        st_ll(dat_base + (cur_bh & (PSLOTS - 1)) * (4 * 8 * MAXG), pack_bf16(lo[0], hi[0]), pack_bf16(lo[1], hi[1]), pack_bf16(lo[2], hi[2]), tag);
                    if (w == 0) {
                        float l = l_run;
                        l += __shfl_xor_sync(0xffffffffu, l, 4);
                        l += __shfl_xor_sync(0xffffffffu, l, 8);
                        l += __shfl_xor_sync(0xffffffffu, l, 16);
                        if (lane == 1) st_ll(hdr_base + (cur_bh & (PSLOTS - 1)) * MAXG, __float_as_uint(m_run), __float_as_uint(l), 0u, tag);
                    }
                }
                m_run = -INFINITY; l_run = 0.f;
#pragma unroll
                for (int mt = 0; mt < 3; mt++) { o[mt][0] = o[mt][1] = o[mt][2] = o[mt][3] = 0.f; }
                cur_bh++;
            }
        };

        while (true) {
            mbar_wait(bar_full + 8 * slot, ph);
            const int unit = meta[slot];
            if (unit < 0) break;
            const int bh = unit >> 8;
            if (bh != cur_bh) {
                if (w == 0 && lane == 0 && cur_bh < 0) PROF(24);
                cp_async_wait_all();
                __syncwarp();
                advance_to(bh);
                const long long t0 = clock64();
                while (true) {
                    if (pre_bh != bh) cp_async16(qraw + lane * 16, g_qll + bh * 32 + lane);
                    cp_async_wait_all();
                    __syncwarp();
                    bool ok = true;
#pragma unroll
                    for (int t = 0; t < 8; t++) {
                        const uint4 r = lds128(qraw + (j * 8 + t) * 16);
                        qf[3 * t] = r.x; qf[3 * t + 1] = r.y; qf[3 * t + 2] = r.z;
                        ok = ok && (r.w == flag);
                    }
                    if (__all_sync(0xffffffffu, ok)) break;
                    pre_bh = -1;
                    __nanosleep(100);
                    spin_check(t0);
                }
                if (w == 0 && lane == 0 && bh == 0) PROF(1);
                pre_bh = bh + 1;
                if (pre_bh < NBH) cp_async16(qraw + lane * 16, g_qll + pre_bh * 32 + lane);
                done_bh = bh - PSLOTS;
                if (done_bh >= 0 && lane == 0) cp_async16(dnraw, g_done + done_bh);
            }
            float s0[4] = {0.f, 0.f, 0.f, 0.f}, s1[4] = {0.f, 0.f, 0.f, 0.f}, s2[4] = {0.f, 0.f, 0.f, 0.f};
            {
                const uint32_t kb = sbase + OFF_RING + slot * TILE_BYTES;
#pragma unroll
                for (int i = 0; i < 4; i++) {
                    uint32_t a[4], b[4], c[4];
                    ldsm4(a, kb + (koff[0] ^ (i * 32)));
                    ldsm4(b, kb + (koff[1] ^ (i * 32)));
                    ldsm4(c, kb + (koff[2] ^ (i * 32)));
                    mma16816(s0, a, qf[2 * i], qf[2 * i + 1]);
                    mma16816(s1, b, qf[8 + 2 * i], qf[8 + 2 * i + 1]);
                    mma16816(s2, c, qf[16 + 2 * i], qf[16 + 2 * i + 1]);
                }
            }
            const float slo = s0[0] + s1[0] + s2[0], shi = s0[2] + s1[2] + s2[2];
            __syncwarp();
            if (lane == 0) mbar_arrive(bar_empty + 8 * slot);
            if (++slot == lim) { slot = 0; ph ^= 1; lim = NS; }
            float* sb = sbuf + par * 64;
            if (j == 0) { sb[16 * w + g] = slo; sb[16 * w + 8 + g] = shi; }
            par ^= 1;
            named_bar(1, NCONS_WARPS * 32);
            float sv[8];
#pragma unroll
            for (int kk = 0; kk < 4; kk++) { sv[2 * kk] = sb[16 * kk + g]; sv[2 * kk + 1] = sb[16 * kk + 8 + g]; }
            float mx = fmaxf(fmaxf(fmaxf(sv[0], sv[1]), fmaxf(sv[2], sv[3])), fmaxf(fmaxf(sv[4], sv[5]), fmaxf(sv[6], sv[7])));
            mx = warp_max(mx);
            const float m_new = fmaxf(m_run, mx);
            const float mc = m_new * SM_SCALE_LOG2;
            const float alpha = ex2(m_run * SM_SCALE_LOG2 - mc);
            m_run = m_new;
            uint32_t pb[4][2];
            float psum = 0.f;
#pragma unroll
            for (int kk = 0; kk < 4; kk++) {
                const float p0 = ex2(fmaf(sv[2 * kk], SM_SCALE_LOG2, -mc));
                const float p1 = ex2(fmaf(sv[2 * kk + 1], SM_SCALE_LOG2, -mc));
                psum += p0 + p1;
                const uint32_t pk = pack_bf16(p0, p1);
                pb[kk][0] = __byte_perm(pk, 0u, sel0);
                pb[kk][1] = __byte_perm(pk, 0u, sel1);
            }
            l_run = l_run * alpha + psum;
#pragma unroll
            for (int mt = 0; mt < 3; mt++) { o[mt][0] *= alpha; o[mt][1] *= alpha; o[mt][2] *= alpha; o[mt][3] *= alpha; }
            mbar_wait(bar_full + 8 * slot, ph);
            {
                const uint32_t vb = sbase + OFF_RING + slot * TILE_BYTES;
#pragma unroll
                for (int k2 = 0; k2 < 4; k2 += 2) {
                    uint32_t a[2][3][4];
#pragma unroll
                    for (int kk = 0; kk < 2; kk++)
#pragma unroll
                        for (int mt = 0; mt < 3; mt++) ldsm4t(a[kk][mt], vb + voff[mt] + (k2 + kk) * 6144);
#pragma unroll
                    for (int kk = 0; kk < 2; kk++)
#pragma unroll
                        for (int mt = 0; mt < 3; mt++) mma16816(o[mt], a[kk][mt], pb[k2 + kk][0], pb[k2 + kk][1]);
                }
            }
            __syncwarp();
            if (lane == 0) mbar_arrive(bar_empty + 8 * slot);
            if (++slot == lim) { slot = 0; ph ^= 1; lim = NS; }
        }
        cp_async_wait_all();
        __syncwarp();
        advance_to(NBH);
        if (w == 0 && lane == 0) {
            PROF(3);
        }
        __syncwarp();
        if (cta == 0 && w == 0 && lane == 0 && EXP_NOMERGE) g_epoch.v = epoch + 1u;
        if (cta < NFIN && !EXP_NOMERGE) {
            TPDECL(4);
            const int nn = lane & 7, sub = lane >> 3;
            const int n = 8 * cta + nn;
            const long long t0 = clock64();
            float* fred = reinterpret_cast<float*>(smem + OFF_FRED);
            const int hw2 = n / 80, r = n - 80 * hw2, idx = r >> 3, jj = idx / 3, tt = idx - 3 * jj;
            const int yoff = sub * 256 + hw2 * 32 + nn * 4 + jj;
            const uint4* zp = g_z + (size_t)(24 * w + sub) * DM + n;
            float hbase = 0.f, yv = 0.f;
#pragma unroll 1
            for (int pass = 0; pass < 2; pass++) {
                if (pass) {
                    if (w == 0) {
                        if (lane == 0) wait_counter(&g_ycnt.v, flag * YCNT, 200);
                        __syncwarp();
                        if (lane < 16) hbase = __bfloat162float(x[sub * DM + n]) + ld_relaxed_f32(g_hacc[epoch & 1] + sub * DM + n);
                    }
                    if (w < NDIRECT - 1) {
                        const uint4* yp = g_y + w * 1024 + yoff;
                        uint4 d = ld_ll(yp);
                        while (d.w != flag) { __nanosleep(100); d = ld_ll(yp); spin_check(t0); }
                        yv = __uint_as_float(tt == 0 ? d.x : (tt == 1 ? d.y : d.z));
                    }
                    const uint4* yp = g_y + (NDIRECT - 1) * 1024 + yoff;
                    uint4 d = ld_ll(yp);
                    while (d.w != flag) { d = ld_ll(yp); spin_check(t0); }
                    if (w == NDIRECT - 1) yv = __uint_as_float(tt == 0 ? d.x : (tt == 1 ? d.y : d.z));
                    __syncwarp();
                    TP(0);
                    const long long t1 = clock64();
                    while (clock64() - t1 < ZWAIT) { }
                }
                uint4 d[6];
#pragma unroll
                for (int s = 0; s < 6; s++) d[s] = ld_ll(zp + (size_t)4 * s * DM);
                if (pass) {
                    while (true) {
                        bool ok = true;
#pragma unroll
                        for (int s = 0; s < 6; s++) { if (d[s].w != flag) { ok = false; d[s] = ld_ll(zp + (size_t)4 * s * DM); } }
                        if (ok) break;
                        spin_check(t0);
                    }
                }
                float z0 = 0.f, z1 = yv;
#pragma unroll
                for (int s = 0; s < 6; s++) { z0 += __uint_as_float(d[s].x); z1 += __uint_as_float(d[s].y); }
                __syncwarp();
                TP(1);
                z0 += __shfl_xor_sync(0xffffffffu, z0, 8); z1 += __shfl_xor_sync(0xffffffffu, z1, 8);
                z0 += __shfl_xor_sync(0xffffffffu, z0, 16); z1 += __shfl_xor_sync(0xffffffffu, z1, 16);
                if (lane < 8) { fred[w * 16 + nn] = z0; fred[w * 16 + 8 + nn] = z1; }
                named_bar(1, NCONS_WARPS * 32);
                if (w == 0 && lane < 16) {
                    const float v = hbase + ((fred[lane] + fred[16 + lane]) + (fred[32 + lane] + fred[48 + lane]));
                    if (pass) out[sub * DM + n] = __float2bfloat16(v);
                }
                if (!pass) named_bar(1, NCONS_WARPS * 32);
            }
            TP(2);
            if (cta == 0 && w == 0 && lane == 0) g_epoch.v = epoch + 1u;
            if (w == 0 && lane == 0) { TPOUT(13, 0); TPOUT(14, 1); TPOUT(7, 2); }
        }
    } else {
        asm volatile("setmaxnreg.inc.sync.aligned.u32 144;");
        if (cta >= NROLE) return;
        const int hw = warp - NCONS_WARPS;
        const int g = lane >> 2, j = lane & 3;
        const int head = cta >> 2, qd = cta & 3;
        int own[3];
#pragma unroll
        for (int t = 0; t < 3; t++) { const int idx = (j < 3) ? 3 * j + t : 9; own[t] = 80 * hw + 16 * (idx >> 1) + 8 * (idx & 1) + g; }
        if (ht < 16) st_ll(g_qll + ((ht >> 3) * NH + head) * 32 + ((ht >> 1) & 3) * 8 + 2 * qd + (ht & 1), 0u, 0u, 0u, 0u);
        float xv[2][3];
        {
            if (cta < 4 * LEAD) asm volatile("cp.async.wait_group 1;" ::: "memory"); else asm volatile("cp.async.wait_group 0;" ::: "memory");
            named_bar(2, NHELP_WARPS * 32);
            if (ht == 0) PROF(23);
            const __nv_bfloat16* xs = reinterpret_cast<const __nv_bfloat16*>(smem + OFF_HROW);
#pragma unroll
            for (int t = 0; t < 3; t++) { xv[0][t] = __bfloat162float(xs[own[t]]); xv[1][t] = __bfloat162float(xs[DM + own[t]]); }
        }
        const uint32_t epoch = *reinterpret_cast<const uint32_t*>(smem + OFF_EPOCH);
        const uint32_t flag = epoch + 1u;
        float* hacc = g_hacc[epoch & 1];
        float* hrow = reinterpret_cast<float*>(smem + OFF_HROW);
        float2* stats = reinterpret_cast<float2*>(smem + OFF_STATS);
        const int krow = (lane & 7) + 8 * (lane >> 4), mhi = (lane >> 3) & 1;
        const long long tstart = clock64();
        auto wait_claims = [&](int target) {
            while (true) {
                const int rem = target - (int)(ld_relaxed_u64(&g_claim.v) - ((unsigned long long)epoch << 14));
                if (rem <= 0) break;
                const unsigned ns = rem > 2000 ? 8000u : (unsigned)rem * 4u;
                __nanosleep(ns < 64u ? 64u : ns);
                spin_check(tstart);
            }
        };
        TPDECL(12);
        auto load_w12 = [&]() {
            mbar_expect_tx(bar_w1, 20480);
#pragma unroll
            for (int i = 0; i < 5; i++) tma2d(sbase + OFF_W1 + i * 4096, &tmW1, cta * 16, i * 128, bar_w1);
            mbar_expect_tx(bar_w2, 20480);
#pragma unroll
            for (int i = 0; i < 10; i++) tma2d(sbase + OFF_W2 + i * 2048, &tmW2, i * 64, cta * 16, bar_w2);
        };

        {
            if (cta >= 4 * LEAD) {
                if (ht == 0) wait_claims((head - LEAD) * TPB - G);
                if (USE_EXTRA && cta >= XCTA) {
#pragma unroll
                    for (int i = NS; i < NSX; i++) mbar_wait(bar_empty + 8 * i, 0);
                }
                named_bar(2, NHELP_WARPS * 32);
                load_wq();
            }
            uint32_t bf[5][2];
            ln_rows2(xv, reinterpret_cast<float*>(smem + OFF_W1), reinterpret_cast<float4*>(smem + OFF_STATS), hw, lane, bf);
            if (ht == 0) PROF(8);
            cp_async_wait_all();
            named_bar(2, NHELP_WARPS * 32);
            if (ht == 0) PROF(9);
            float* red = reinterpret_cast<float*>(smem + OFF_RED_Q);
            float acc[3][4];
#pragma unroll
            for (int mt = 0; mt < 3; mt++) { acc[mt][0] = acc[mt][1] = acc[mt][2] = acc[mt][3] = 0.f; }
#pragma unroll
            for (int i = 0; i < 5; i++) {
                const uint32_t rowaddr = sbase + OFF_WQO + (16 * (5 * hw + i) + krow) * 96 + mhi * 16;
#pragma unroll
                for (int mt = 0; mt < 3; mt++) {
                    uint32_t a[4];
                    ldsm4t(a, rowaddr + mt * 32);
                    mma16816(acc[mt], a, bf[i][0], bf[i][1]);
                }
            }
            if (j == 0) {
#pragma unroll
                for (int mt = 0; mt < 3; mt++) {
                    red[hw * 96 + 16 * mt + g] = acc[mt][0];
                    red[hw * 96 + 48 + 16 * mt + g] = acc[mt][1];
                    red[hw * 96 + 16 * mt + 8 + g] = acc[mt][2];
                    red[hw * 96 + 48 + 16 * mt + 8 + g] = acc[mt][3];
                }
            }
            named_bar(2, NHELP_WARPS * 32);
            if (ht < 96) {
                float s = 0.f;
#pragma unroll
                for (int k = 0; k < 8; k++) s += red[k * 96 + ht];
                red[8 * 96 + ht] = s;
            }
            named_bar(2, NHELP_WARPS * 32);
            if (ht < 16) {
                const int b = ht >> 3, jj = (ht >> 1) & 3, e2 = ht & 1;
                uint32_t fw[3];
#pragma unroll
                for (int r = 0; r < 3; r++) {
                    const int rl = 3 * e2 + r;
                    const int col = 16 * (rl >> 1) + 8 * (rl & 1) + 2 * jj;
                    fw[r] = pack_bf16(red[8 * 96 + b * 48 + col], red[8 * 96 + b * 48 + col + 1]);
                }
                st_ll(g_qll + (b * NH + head) * 32 + jj * 8 + 2 * qd + e2, fw[0], fw[1], fw[2], flag);
            }
            __syncwarp();
            named_bar(2, NHELP_WARPS * 32);
            if (ht == 0) {
                PROF(10);
                asm volatile("fence.proxy.async;" ::: "memory");
                mbar_expect_tx(bar_wo, 61440);
#pragma unroll
                for (int i = 0; i < 10; i++) tma2d(sbase + OFF_WQO + i * 6144, &tmWo, i * 64, cta * 48, bar_wo);
                if (cta < NMLP && W12_AT == 0) load_w12();
            }
            if (head >= NH - NDIRECT) st_ll(g_y + ((head - (NH - NDIRECT)) * 4 + qd) * 256 + ht, 0u, 0u, 0u, 0u);
            if (cta < NMLP) {
#pragma unroll
                for (int i = 0; i < 3; i++) if (ht + 256 * i < DM) st_ll(g_z + (size_t)cta * DM + ht + 256 * i, 0u, 0u, 0u, 0u);
            }
            if (cta == 0) {
#pragma unroll
                for (int i = 0; i < 5; i++) g_hacc[(epoch + 1) & 1][ht + 256 * i] = 0.f;
            }
        }

        if (EXP_NOMERGE) return;
        __nv_bfloat16* obf = reinterpret_cast<__nv_bfloat16*>(smem + OFF_OBF);
        uint32_t wof[3][5][4];
        mbar_wait(bar_wo, 0);
#pragma unroll
        for (int i = 0; i < 5; i++) {
            const int mt = 5 * hw + i;
            const uint32_t addr = sbase + OFF_WQO + (mt >> 2) * 6144 + krow * 128 + (((2 * (mt & 3) + mhi) ^ (krow & 7)) << 4);
#pragma unroll
            for (int ks = 0; ks < 3; ks++) ldsm4t(wof[ks][i], addr + ks * 2048);
        }
#pragma unroll 1
        for (int b = 0; b < NB; b++) {
            const int bh = b * NH + head;
            const bool last = (bh == NBH - 1), direct = (bh >= NBH - NDIRECT), eager = (bh >= NBH - 2);
            if (ht == 0) wait_claims(eager ? (bh + 1) * TPB - G : min((bh + 1) * TPB + MERGE_MARGIN * G, NUNITS - G));
            named_bar(2, NHELP_WARPS * 32);
            uint4 hd[5], dt[5];
            const uint32_t tag = flag * 8u + (uint32_t)(bh >> 3);
#pragma unroll 1
            for (int pass = last ? 0 : 1; pass < 2; pass++) {
                const uint32_t pend = pass ? tag - 1u : tag;
#pragma unroll
                for (int s = 0; s < 5; s++) {
                    const uint32_t st = (lane + 32 * s < G) ? pend : tag;
                    hd[s] = make_uint4(0xff800000u, 0u, 0u, st); dt[s] = make_uint4(0u, 0u, 0u, st);
                }
                {
                    const uint4* hp = g_hdr + (bh & (PSLOTS - 1)) * MAXG + lane;
                    const uint4* dp = g_dat + (((bh & (PSLOTS - 1)) * 4 + qd) * 8 + hw) * MAXG + lane;
                    while (true) {
#pragma unroll
                        for (int s = 0; s < 5; s++) {
                            if (dt[s].w != tag) dt[s] = ld_ll(dp + 32 * s);
                            if (hd[s].w != tag) hd[s] = ld_ll(hp + 32 * s);
                        }
                        bool ok = true;
#pragma unroll
                        for (int s = 0; s < 5; s++) ok = ok && dt[s].w == tag && hd[s].w == tag;
                        if (__all_sync(0xffffffffu, ok)) break;
                        if (!eager) __nanosleep(500);
                        spin_check(tstart);
                    }
                }
                TP(6);
                const float M = warp_max(fmaxf(fmaxf(fmaxf(__uint_as_float(hd[0].x), __uint_as_float(hd[1].x)),
                                               fmaxf(__uint_as_float(hd[2].x), __uint_as_float(hd[3].x))), __uint_as_float(hd[4].x)));
                float a[8];
#pragma unroll
                for (int i = 0; i < 8; i++) a[i] = 0.f;
#pragma unroll
                for (int s = 0; s < 5; s++) {
                    const float wgt = ex2((__uint_as_float(hd[s].x) - M) * SM_SCALE_LOG2);
                    a[0] = fmaf(wgt, __uint_as_float(dt[s].x << 16), a[0]);
                    a[1] = fmaf(wgt, __uint_as_float(dt[s].x & 0xffff0000u), a[1]);
                    a[2] = fmaf(wgt, __uint_as_float(dt[s].y << 16), a[2]);
                    a[3] = fmaf(wgt, __uint_as_float(dt[s].y & 0xffff0000u), a[3]);
                    a[4] = fmaf(wgt, __uint_as_float(dt[s].z << 16), a[4]);
                    a[5] = fmaf(wgt, __uint_as_float(dt[s].z & 0xffff0000u), a[5]);
                    a[6] = fmaf(wgt, __uint_as_float(hd[s].y), a[6]);
                }
                {
                    const bool up16 = lane & 16, up8 = lane & 8, up4 = lane & 4;
#pragma unroll
                    for (int i = 0; i < 4; i++) a[i] = (up16 ? a[i + 4] : a[i]) + __shfl_xor_sync(0xffffffffu, up16 ? a[i] : a[i + 4], 16);
#pragma unroll
                    for (int i = 0; i < 2; i++) a[i] = (up8 ? a[i + 2] : a[i]) + __shfl_xor_sync(0xffffffffu, up8 ? a[i] : a[i + 2], 8);
                    a[0] = (up4 ? a[1] : a[0]) + __shfl_xor_sync(0xffffffffu, up4 ? a[0] : a[1], 4);
                    a[0] += __shfl_xor_sync(0xffffffffu, a[0], 2);
                    a[0] += __shfl_xor_sync(0xffffffffu, a[0], 1);
                    const float Lt = __shfl_sync(0xffffffffu, a[0], 24);
                    if (g < 6 && j == 0) obf[8 * g + hw] = __float2bfloat16(__fdividef(a[0], Lt));
                }
                named_bar(2, NHELP_WARPS * 32);
                TP(7);
                float yv[10];
                {
                    const uint32_t* ow = reinterpret_cast<const uint32_t*>(obf);
                    uint32_t bq[3][2];
#pragma unroll
                    for (int ks = 0; ks < 3; ks++) { bq[ks][0] = ow[8 * ks + j]; bq[ks][1] = ow[8 * ks + 4 + j]; }
                    float acc[5][4];
#pragma unroll
                    for (int i = 0; i < 5; i++) acc[i][0] = acc[i][1] = acc[i][2] = acc[i][3] = 0.f;
#pragma unroll
                    for (int ks = 0; ks < 3; ks++) {
#pragma unroll
                        for (int i = 0; i < 5; i++) mma16816(acc[i], wof[ks][i], bq[ks][0], bq[ks][1]);
                    }
#pragma unroll
                    for (int i = 0; i < 5; i++) { yv[2 * i] = acc[i][0]; yv[2 * i + 1] = acc[i][2]; }
                }
                const float y0 = j == 0 ? yv[0] : (j == 1 ? yv[3] : (j == 2 ? yv[6] : yv[9]));
                const float y1 = j == 0 ? yv[1] : (j == 1 ? yv[4] : yv[7]);
                const float y2 = j == 0 ? yv[2] : (j == 1 ? yv[5] : yv[8]);
                if (pass) {
                    if (direct) {
                        st_ll(g_y + ((bh - (NBH - NDIRECT)) * 4 + qd) * 256 + ht, __float_as_uint(y0), __float_as_uint(y1), __float_as_uint(y2), flag);
                    } else {
                        red_add_f32(hacc + b * DM + own[0], y0);
                        if (j < 3) { red_add_f32(hacc + b * DM + own[1], y1); red_add_f32(hacc + b * DM + own[2], y2); }
                    }
                }
                TP(8);
                named_bar(2, NHELP_WARPS * 32);
            }
            if (ht == 0) {
                fence_gpu();
                if (!direct) red_add_u32(&g_ycnt.v, 1u);
                asm volatile("st.relaxed.gpu.global.u32 [%0], %1;" :: "l"(reinterpret_cast<unsigned*>(g_done + bh) + qd), "r"(flag) : "memory");
            }
        }
        if (ht == 0) { TPOUT(11, 6); TPOUT(12, 7); TPOUT(4, 8); }
        if (cta >= NMLP) return;

        if (W12_AT != 0 && ht == 0) { wait_claims(NUNITS - G - W12_AT); load_w12(); }
        float hpre[3] = {0.f, 0.f, 0.f};
        uint32_t bf0[5][2], w1f[5][4], w2f[5][4];
#pragma unroll
        for (int i = 0; i < 5; i++) { bf0[i][0] = bf0[i][1] = 0u; }
        mbar_wait(bar_w1, 0);
#pragma unroll
        for (int i = 0; i < 5; i++) ldsm4t(w1f[i], sbase + OFF_W1 + (16 * (5 * hw + i) + krow) * 32 + mhi * 16);
        mbar_wait(bar_w2, 0);
#pragma unroll
        for (int i = 0; i < 5; i++) {
            const int mt = 5 * hw + i;
            ldsm4t(w2f[i], sbase + OFF_W2 + (mt >> 2) * 2048 + krow * 128 + (((2 * (mt & 3) + mhi) ^ (krow & 7)) << 4));
        }
        float* red1 = reinterpret_cast<float*>(smem + OFF_RED1);
        uint4* const zout = g_z + (size_t)cta * DM + 80 * hw + g;
#pragma unroll 1
        for (int pass = 0; pass < 2; pass++) {
            if (pass) {
                if (ht == 0) wait_counter(&g_ycnt.v, flag * YCNT, 200);
                named_bar(2, NHELP_WARPS * 32);
                float h0[3];
#pragma unroll
                for (int t = 0; t < 3; t++) {
                    h0[t] = xv[0][t] + ld_relaxed_f32(hacc + own[t]);
                    hpre[t] = xv[1][t] + ld_relaxed_f32(hacc + DM + own[t]);
                }
                ln_row(h0, hrow, stats, hw, lane, bf0);
                TP(9);
#pragma unroll 1
                for (int dd = 0; dd < NDIRECT - 1; dd++) {
                    if (ht < 4) {
                        const uint4* yp = g_y + (dd * 4 + ht) * 256;
                        while (ld_ll(yp).w != flag) { __nanosleep(64); spin_check(tstart); }
                    }
                    named_bar(2, NHELP_WARPS * 32);
                    uint4 y[4];
                    const uint4* yp = g_y + dd * 1024 + ht;
#pragma unroll
                    for (int s = 0; s < 4; s++) y[s] = ld_ll(yp + s * 256);
#pragma unroll
                    for (int s = 0; s < 4; s++) {
                        while (y[s].w != flag) { y[s] = ld_ll(yp + s * 256); spin_check(tstart); }
                        hpre[0] += __uint_as_float(y[s].x); hpre[1] += __uint_as_float(y[s].y); hpre[2] += __uint_as_float(y[s].z);
                    }
                }
                TP(10);
                if (ht < 4) {
                    const uint4* yp = g_y + ((NDIRECT - 1) * 4 + ht) * 256;
                    while (ld_ll(yp).w != flag) spin_check(tstart);
                }
                named_bar(2, NHELP_WARPS * 32);
            }
            TP(0);
            uint4 y[4];
            const uint4* yp = g_y + (NDIRECT - 1) * 1024 + ht;
#pragma unroll
            for (int s = 0; s < 4; s++) y[s] = ld_ll(yp + s * 256);
            if (pass) {
#pragma unroll
                for (int s = 0; s < 4; s++) while (y[s].w != flag) { y[s] = ld_ll(yp + s * 256); spin_check(tstart); }
            }
            float v[3];
            v[0] = hpre[0] + ((__uint_as_float(y[0].x) + __uint_as_float(y[1].x)) + (__uint_as_float(y[2].x) + __uint_as_float(y[3].x)));
            v[1] = hpre[1] + ((__uint_as_float(y[0].y) + __uint_as_float(y[1].y)) + (__uint_as_float(y[2].y) + __uint_as_float(y[3].y)));
            v[2] = hpre[2] + ((__uint_as_float(y[0].z) + __uint_as_float(y[1].z)) + (__uint_as_float(y[2].z) + __uint_as_float(y[3].z)));
            TP(1);
            uint32_t fr[5][2];
            ln_row(v, hrow, stats + 8, hw, lane, fr);
            TP(2);
            float acc0[4] = {0.f, 0.f, 0.f, 0.f}, acc1[4] = {0.f, 0.f, 0.f, 0.f};
#pragma unroll
            for (int i = 0; i < 5; i++) {
                const uint32_t b0 = (g == 0) ? bf0[i][0] : ((g == 1) ? fr[i][0] : 0u);
                const uint32_t b1 = (g == 0) ? bf0[i][1] : ((g == 1) ? fr[i][1] : 0u);
                if (i & 1) mma16816(acc1, w1f[i], b0, b1); else mma16816(acc0, w1f[i], b0, b1);
            }
            if (j == 0) {
                red1[hw * 32 + g] = acc0[0] + acc1[0]; red1[hw * 32 + 16 + g] = acc0[1] + acc1[1];
                red1[hw * 32 + 8 + g] = acc0[2] + acc1[2]; red1[hw * 32 + 16 + 8 + g] = acc0[3] + acc1[3];
            }
            named_bar(2, NHELP_WARPS * 32);
            TP(3);
            uint32_t b0, b1;
            {
                const float* rp = red1 + (g & 1) * 16 + 2 * j;
                float2 p[8], q[8];
#pragma unroll
                for (int k = 0; k < 8; k++) { p[k] = *reinterpret_cast<const float2*>(rp + k * 32); q[k] = *reinterpret_cast<const float2*>(rp + k * 32 + 8); }
                const float lx = ((p[0].x + p[1].x) + (p[2].x + p[3].x)) + ((p[4].x + p[5].x) + (p[6].x + p[7].x));
                const float ly = ((p[0].y + p[1].y) + (p[2].y + p[3].y)) + ((p[4].y + p[5].y) + (p[6].y + p[7].y));
                const float hx = ((q[0].x + q[1].x) + (q[2].x + q[3].x)) + ((q[4].x + q[5].x) + (q[6].x + q[7].x));
                const float hy = ((q[0].y + q[1].y) + (q[2].y + q[3].y)) + ((q[4].y + q[5].y) + (q[6].y + q[7].y));
                b0 = pack_bf16(fmaxf(lx, 0.f), fmaxf(ly, 0.f));
                b1 = pack_bf16(fmaxf(hx, 0.f), fmaxf(hy, 0.f));
            }
            TP(4);
            float z[5][4];
#pragma unroll
            for (int i = 0; i < 5; i++) { z[i][0] = z[i][1] = z[i][2] = z[i][3] = 0.f; mma16816(z[i], w2f[i], b0, b1); }
            {
                const bool j1 = j & 1, j2 = j & 2;
                const float za0 = j2 ? (j1 ? z[1][2] : z[1][0]) : (j1 ? z[0][2] : z[0][0]), zb0 = j2 ? (j1 ? z[1][3] : z[1][1]) : (j1 ? z[0][3] : z[0][1]);
                const float za1 = j2 ? (j1 ? z[3][2] : z[3][0]) : (j1 ? z[2][2] : z[2][0]), zb1 = j2 ? (j1 ? z[3][3] : z[3][1]) : (j1 ? z[2][3] : z[2][1]);
                const float za2 = j1 ? z[4][2] : z[4][0], zb2 = j1 ? z[4][3] : z[4][1];
                if (pass) {
                    st_ll(zout + 8 * j, __float_as_uint(za0), __float_as_uint(zb0), 0u, flag);
                    st_ll(zout + 8 * (4 + j), __float_as_uint(za1), __float_as_uint(zb1), 0u, flag);
                    if (j < 2) st_ll(zout + 8 * (8 + j), __float_as_uint(za2), __float_as_uint(zb2), 0u, flag);
                }
            }
            TP(5);
            if (!pass) named_bar(2, NHELP_WARPS * 32);
        }
        if (ht == 0) { TPOUT(16, 0); TPOUT(17, 1); TPOUT(18, 2); TPOUT(19, 3); TPOUT(20, 4); TPOUT(21, 5); TPOUT(5, 9); TPOUT(6, 10); }
    }
}

typedef CUresult (*EncodeTiledFn)(CUtensorMap*, CUtensorMapDataType, cuuint32_t, void*, const cuuint64_t*, const cuuint64_t*,
                                  const cuuint32_t*, const cuuint32_t*, CUtensorMapInterleave, CUtensorMapSwizzle,
                                  CUtensorMapL2promotion, CUtensorMapFloatOOBfill);

static void make_map(EncodeTiledFn enc, CUtensorMap* tm, const void* base, uint64_t cols, uint64_t rows,
                     uint32_t box_cols, uint32_t box_rows, CUtensorMapSwizzle swz) {
    cuuint64_t dims[2] = {cols, rows};
    cuuint64_t strides[1] = {cols * 2};
    cuuint32_t box[2] = {box_cols, box_rows};
    cuuint32_t es[2] = {1, 1};
    enc(tm, CU_TENSOR_MAP_DATA_TYPE_BFLOAT16, 2, const_cast<void*>(base), dims, strides, box, es,
        CU_TENSOR_MAP_INTERLEAVE_NONE, swz, CU_TENSOR_MAP_L2_PROMOTION_NONE, CU_TENSOR_MAP_FLOAT_OOB_FILL_NONE);
}

}

extern "C" void kernel_launch(void* const* d_in, const int* in_sizes, int n_in, void* d_out, int out_size) {
    using namespace fused;
    (void)in_sizes; (void)n_in; (void)out_size;
    static EncodeTiledFn enc = nullptr;
    static int grid = 0;
    if (!enc) {
        void* fn = nullptr;
        cudaDriverEntryPointQueryResult qr;
        cudaGetDriverEntryPoint("cuTensorMapEncodeTiled", &fn, cudaEnableDefault, &qr);
        enc = (EncodeTiledFn)fn;
        int dev = 0, sms = 0;
        cudaGetDevice(&dev);
        cudaDeviceGetAttribute(&sms, cudaDevAttrMultiProcessorCount, dev);
        grid = sms < MAXG ? sms : MAXG;
        cudaFuncSetAttribute(fused_decode_kernel, cudaFuncAttributeMaxDynamicSharedMemorySize, SMEM_BYTES);
    }
    const __nv_bfloat16* x = (const __nv_bfloat16*)d_in[0];
    CUtensorMap tmK, tmV, tmWo, tmW1, tmW2;
    make_map(enc, &tmK, d_in[1], 64, (uint64_t)NBH * SK * 3, 64, 192, CU_TENSOR_MAP_SWIZZLE_128B);
    make_map(enc, &tmV, d_in[2], 64, (uint64_t)NBH * SK * 3, 64, 192, CU_TENSOR_MAP_SWIZZLE_128B);
    make_map(enc, &tmWo, d_in[4], DM, NH * DH, 64, 48, CU_TENSOR_MAP_SWIZZLE_128B);
    make_map(enc, &tmW1, d_in[6], DFF, DM, 16, 128, CU_TENSOR_MAP_SWIZZLE_NONE);
    make_map(enc, &tmW2, d_in[7], DM, DFF, 64, 16, CU_TENSOR_MAP_SWIZZLE_128B);
    fused_decode_kernel<<<grid, NTHREADS, SMEM_BYTES>>>(tmK, tmV, tmWo, tmW1, tmW2, x, (const __nv_bfloat16*)d_in[3], (__nv_bfloat16*)d_out);
}
```

```cpp
#include <cuda_runtime.h>
#include <cuda_bf16.h>
#include <cuda.h>
#include <stdint.h>

namespace fused {

constexpr int NB = 2, DM = 640, NH = 32, SK = 16384, DH = 192, DFF = 1536;
constexpr int TILE = 64;
constexpr int TPB = SK / TILE;
constexpr int NBH = NB * NH;
constexpr int NUNITS = NBH * TPB;
constexpr int TILE_BYTES = TILE * DH * 2;
constexpr int NS = 5;
constexpr int NSX = 9;
constexpr int XCTA = 24;
#define LEADV 32
constexpr int LEAD = LEADV;
constexpr int MAXG = 132;
constexpr int NROLE = 128;
constexpr int NMLP = 96;
constexpr int NFIN = 80;

#define NDIR 4
constexpr int NDIRECT = NDIR;
constexpr int YCNT = NROLE * NB - 4 * NDIRECT;

#define MERGE_MARGIN 2
#define W12_AT 0
#define START_DELAY 0
#define USE_EXTRA 0
#define EXP_NOFLUSH 0
#define EXP_NOMERGE 0
#define DIRECT_POLL 0
#define QPOLL_NS 300
#define ENDGAME 0
#define W3D 1
#define EXP_SKIP 0
#define EXP2 0
#define YSLEEP 200
#define ZWAIT 3300
constexpr int PSLOTS = 8;

constexpr int NCONS_WARPS = 4;
constexpr int NHELP_WARPS = 8;
constexpr int NTHREADS = (NCONS_WARPS + NHELP_WARPS + 1) * 32;

constexpr int OFF_RING = 0;
constexpr int OFF_WQO = OFF_RING + NS * TILE_BYTES;
constexpr int OFF_W1 = OFF_WQO + 61440;
constexpr int OFF_W2 = OFF_W1 + 20480;
constexpr int OFF_MISC = OFF_W2 + 20480;
constexpr int OFF_QRAW = OFF_MISC;
constexpr int OFF_DONE = OFF_QRAW + 2048;
constexpr int OFF_HROW = OFF_DONE + 64;
constexpr int OFF_RED1 = OFF_HROW + 2560;
constexpr int OFF_SBUF = OFF_RED1 + 1024;
constexpr int OFF_STATS = OFF_SBUF + 512;
constexpr int OFF_FRED = OFF_STATS + 128;
constexpr int OFF_OBF = OFF_FRED + 384;
constexpr int OFF_META = OFF_OBF + 128;
constexpr int OFF_EPOCH = OFF_META + 48;
constexpr int OFF_BARS = OFF_EPOCH + 16;
constexpr int NBARS = 2 * NSX + 4;
constexpr int SMEM_BYTES = OFF_BARS + NBARS * 8 + 8;
constexpr int OFF_RED_Q = OFF_W2;
static_assert(SMEM_BYTES <= 232448, "smem");

constexpr float SM_SCALE = 0.07216878364870322f;
constexpr float LOG2E = 1.4426950408889634f;
constexpr float LN_EPS = 1e-5f;

struct __align__(128) Counter64 { unsigned long long v; unsigned long long pad[15]; };
struct __align__(128) Counter32 { unsigned v; unsigned pad[31]; };
__device__ Counter64 g_claim;
__device__ Counter32 g_ycnt;
__device__ Counter32 g_epoch;
__device__ __align__(128) uint4 g_qll[NBH * 32];
__device__ __align__(128) uint4 g_hdr[PSLOTS * MAXG];
__device__ __align__(128) uint4 g_done[NBH];
__device__ __align__(128) uint4 g_dat[PSLOTS * 4 * 8 * MAXG];
__device__ __align__(128) float g_hacc[2][NB * DM];
__device__ __align__(128) uint4 g_y[NDIRECT * 4 * 256];
__device__ __align__(128) uint4 g_z[NMLP * DM];

#define TPDECL(n) do { } while (0)
#define TP(i) do { } while (0)
#define TPOUT(slot, i) do { } while (0)
#define PROF(slot) do { } while (0)
#define PROF_REF() do { } while (0)
#define PROF_REF2() do { } while (0)

__device__ __forceinline__ uint32_t smem_u32(const void* p) { return (uint32_t)__cvta_generic_to_shared(p); }
__device__ __forceinline__ void mbar_init(uint32_t bar, uint32_t cnt) {
    asm volatile("mbarrier.init.shared::cta.b64 [%0], %1;" :: "r"(bar), "r"(cnt) : "memory");
}
__device__ __forceinline__ void mbar_expect_tx(uint32_t bar, uint32_t bytes) {
    asm volatile("mbarrier.arrive.expect_tx.shared::cta.b64 _, [%0], %1;" :: "r"(bar), "r"(bytes) : "memory");
}
__device__ __forceinline__ void mbar_arrive(uint32_t bar) {
    asm volatile("mbarrier.arrive.shared::cta.b64 _, [%0];" :: "r"(bar) : "memory");
}
__device__ __forceinline__ bool mbar_try(uint32_t bar, uint32_t parity) {
    uint32_t ok;
    asm volatile("{\n.reg .pred p;\nmbarrier.try_wait.parity.shared::cta.b64 p, [%1], %2;\nselp.u32 %0, 1, 0, p;\n}"
                 : "=r"(ok) : "r"(bar), "r"(parity) : "memory");
    return ok != 0;
}
constexpr long long SPIN_LIMIT = 4000000000LL;
__device__ __forceinline__ void spin_check(long long t0) { if (clock64() - t0 > SPIN_LIMIT) __trap(); }
__device__ __forceinline__ void mbar_wait(uint32_t bar, uint32_t parity) {
    if (mbar_try(bar, parity)) return;
    const long long t0 = clock64();
    while (!mbar_try(bar, parity)) spin_check(t0);
}
__device__ __forceinline__ void tma2d(uint32_t dst, const CUtensorMap* tm, int c0, int c1, uint32_t bar) {
    asm volatile("cp.async.bulk.tensor.2d.shared::cluster.global.mbarrier::complete_tx::bytes [%0], [%1, {%3, %4}], [%2];"
                 :: "r"(dst), "l"(tm), "r"(bar), "r"(c0), "r"(c1) : "memory");
}
__device__ __forceinline__ void tma2d_hint(uint32_t dst, const CUtensorMap* tm, int c0, int c1, uint32_t bar, uint64_t pol) {
    asm volatile("cp.async.bulk.tensor.2d.shared::cluster.global.mbarrier::complete_tx::bytes.L2::cache_hint [%0], [%1, {%3, %4}], [%2], %5;"
                 :: "r"(dst), "l"(tm), "r"(bar), "r"(c0), "r"(c1), "l"(pol) : "memory");
}
__device__ __forceinline__ void tma3d(uint32_t dst, const CUtensorMap* tm, int c0, int c1, int c2, uint32_t bar) {
    asm volatile("cp.async.bulk.tensor.3d.shared::cluster.global.mbarrier::complete_tx::bytes [%0], [%1, {%3, %4, %5}], [%2];"
                 :: "r"(dst), "l"(tm), "r"(bar), "r"(c0), "r"(c1), "r"(c2) : "memory");
}
__device__ __forceinline__ void bulk_g2s(uint32_t dst, const void* src, uint32_t bytes, uint32_t bar) {
    asm volatile("cp.async.bulk.shared::cluster.global.mbarrier::complete_tx::bytes [%0], [%1], %2, [%3];"
                 :: "r"(dst), "l"(src), "r"(bytes), "r"(bar) : "memory");
}
__device__ __forceinline__ void named_bar(int id, int nthreads) {
    asm volatile("bar.sync %0, %1;" :: "r"(id), "r"(nthreads) : "memory");
}
__device__ __forceinline__ void ldsm4(uint32_t (&r)[4], uint32_t addr) {
    asm volatile("ldmatrix.sync.aligned.m8n8.x4.shared.b16 {%0,%1,%2,%3}, [%4];"
                 : "=r"(r[0]), "=r"(r[1]), "=r"(r[2]), "=r"(r[3]) : "r"(addr) : "memory");
}
__device__ __forceinline__ void ldsm4t(uint32_t (&r)[4], uint32_t addr) {
    asm volatile("ldmatrix.sync.aligned.m8n8.x4.trans.shared.b16 {%0,%1,%2,%3}, [%4];"
                 : "=r"(r[0]), "=r"(r[1]), "=r"(r[2]), "=r"(r[3]) : "r"(addr) : "memory");
}
__device__ __forceinline__ void mma16816(float (&c)[4], const uint32_t (&a)[4], uint32_t b0, uint32_t b1) {
    asm volatile("mma.sync.aligned.m16n8k16.row.col.f32.bf16.bf16.f32 {%0,%1,%2,%3}, {%4,%5,%6,%7}, {%8,%9}, {%0,%1,%2,%3};"
                 : "+f"(c[0]), "+f"(c[1]), "+f"(c[2]), "+f"(c[3])
                 : "r"(a[0]), "r"(a[1]), "r"(a[2]), "r"(a[3]), "r"(b0), "r"(b1));
}
__device__ __forceinline__ uint32_t pack_bf16(float lo, float hi) {
    uint32_t r;
    asm("cvt.rn.bf16x2.f32 %0, %1, %2;" : "=r"(r) : "f"(hi), "f"(lo));
    return r;
}
__device__ __forceinline__ float rbf(float x) { return __uint_as_float(pack_bf16(0.f, x) & 0xffff0000u); }
__device__ __forceinline__ float ex2(float x) { float y; asm("ex2.approx.ftz.f32 %0, %1;" : "=f"(y) : "f"(x)); return y; }
__device__ __forceinline__ void st_ll(uint4* p, uint32_t a, uint32_t b, uint32_t c, uint32_t d) {
    unsigned long long lo = (unsigned long long)a | ((unsigned long long)b << 32);
    unsigned long long hi = (unsigned long long)c | ((unsigned long long)d << 32);
    asm volatile("{\n.reg .b128 t;\nmov.b128 t, {%1, %2};\nst.relaxed.gpu.global.b128 [%0], t;\n}" :: "l"(p), "l"(lo), "l"(hi) : "memory");
}
__device__ __forceinline__ uint4 ld_ll(const uint4* p) {
    unsigned long long lo, hi;
    asm volatile("{\n.reg .b128 t;\nld.relaxed.gpu.global.b128 t, [%2];\nmov.b128 {%0, %1}, t;\n}" : "=l"(lo), "=l"(hi) : "l"(p) : "memory");
    uint4 r; r.x = (uint32_t)lo; r.y = (uint32_t)(lo >> 32); r.z = (uint32_t)hi; r.w = (uint32_t)(hi >> 32);
    return r;
}
__device__ __forceinline__ unsigned ld_relaxed_u32(const unsigned* p) {
    unsigned v; asm volatile("ld.relaxed.gpu.global.u32 %0, [%1];" : "=r"(v) : "l"(p) : "memory"); return v;
}
__device__ __forceinline__ unsigned long long ld_relaxed_u64(const unsigned long long* p) {
    unsigned long long v; asm volatile("ld.relaxed.gpu.global.u64 %0, [%1];" : "=l"(v) : "l"(p) : "memory"); return v;
}
__device__ __forceinline__ float ld_relaxed_f32(const float* p) {
    float v; asm volatile("ld.relaxed.gpu.global.f32 %0, [%1];" : "=f"(v) : "l"(p) : "memory"); return v;
}
__device__ __forceinline__ void fence_gpu() { asm volatile("fence.acq_rel.gpu;" ::: "memory"); }
__device__ __forceinline__ void red_add_u32(unsigned* p, unsigned v) {
    asm volatile("red.relaxed.gpu.global.add.u32 [%0], %1;" :: "l"(p), "r"(v) : "memory");
}
__device__ __forceinline__ void red_add_f32(float* p, float v) {
    asm volatile("red.relaxed.gpu.global.add.f32 [%0], %1;" :: "l"(p), "f"(v) : "memory");
}
__device__ __forceinline__ void wait_counter(const unsigned* p, unsigned target, unsigned sleep_ns) {
    const long long t0 = clock64();
    while (true) {
        unsigned v;
        asm volatile("ld.acquire.gpu.global.u32 %0, [%1];" : "=r"(v) : "l"(p) : "memory");
        if ((int)(v - target) >= 0) break;
        __nanosleep(sleep_ns); spin_check(t0);
    }
}
__device__ __forceinline__ void cp_async16(uint32_t dst, const void* src) {
    asm volatile("cp.async.cg.shared.global [%0], [%1], 16;" :: "r"(dst), "l"(src) : "memory");
}
__device__ __forceinline__ void cp_async_wait_all() { asm volatile("cp.async.wait_all;" ::: "memory"); }
__device__ __forceinline__ uint4 lds128(uint32_t addr) {
    uint4 r;
    asm volatile("ld.shared.v4.u32 {%0,%1,%2,%3}, [%4];" : "=r"(r.x), "=r"(r.y), "=r"(r.z), "=r"(r.w) : "r"(addr) : "memory");
    return r;
}
__device__ __forceinline__ float warp_max(float v) {
    int i = __float_as_int(v);
    i ^= (i >> 31) & 0x7fffffff;
    i = __reduce_max_sync(0xffffffffu, i);
    i ^= (i >> 31) & 0x7fffffff;
    return __int_as_float(i);
}

__device__ __forceinline__ void ln_row(const float (&v)[3], float* hrow, float2* stats, int hw, int lane, uint32_t (&fr)[5][2]) {
    const int g = lane >> 2, j = lane & 3;
    const bool full = j < 3;
    float* hp = hrow + 80 * hw + g;
    __syncwarp();
    {
        const int i0 = 3 * j;
        hp[16 * (i0 >> 1) + 8 * (i0 & 1)] = v[0];
        if (full) {
            hp[16 * ((i0 + 1) >> 1) + 8 * ((i0 + 1) & 1)] = v[1];
            hp[16 * ((i0 + 2) >> 1) + 8 * ((i0 + 2) & 1)] = v[2];
        }
    }
    const float c = __shfl_sync(0xffffffffu, v[0], 0);
    const float d0 = v[0] - c, d1 = full ? v[1] - c : 0.f, d2 = full ? v[2] - c : 0.f;
    float s1 = d0 + d1 + d2, s2 = d0 * d0 + d1 * d1 + d2 * d2;
#pragma unroll
    for (int o = 16; o >= 1; o >>= 1) { s1 += __shfl_xor_sync(0xffffffffu, s1, o); s2 += __shfl_xor_sync(0xffffffffu, s2, o); }
    if (lane == 0) stats[hw] = make_float2(c + s1 * (1.0f / 80.0f), s2 - s1 * s1 * (1.0f / 80.0f));
    named_bar(2, NHELP_WARPS * 32);
    const float4* sp = reinterpret_cast<const float4*>(stats);
    const float4 a = sp[0], b = sp[1], cc = sp[2], d = sp[3];
    const float mean = (((a.x + a.z) + (b.x + b.z)) + ((cc.x + cc.z) + (d.x + d.z))) * 0.125f;
    const float e0 = a.x - mean, e1 = a.z - mean, e2 = b.x - mean, e3 = b.z - mean, e4 = cc.x - mean, e5 = cc.z - mean, e6 = d.x - mean, e7 = d.z - mean;
    const float m2 = (((a.y + a.w) + (b.y + b.w)) + ((cc.y + cc.w) + (d.y + d.w))) +
                     80.0f * (((e0 * e0 + e1 * e1) + (e2 * e2 + e3 * e3)) + ((e4 * e4 + e5 * e5) + (e6 * e6 + e7 * e7)));
    const float mb = rbf(mean);
    const float rinv = __frcp_rn(rbf(__fsqrt_rn(rbf(rbf(fmaxf(m2, 0.f) * (1.0f / DM)) + LN_EPS))));
    const float* fp = hrow + 80 * hw + 2 * j;
#pragma unroll
    for (int i = 0; i < 5; i++) {
        const float2 p = *reinterpret_cast<const float2*>(fp + 16 * i);
        const float2 q = *reinterpret_cast<const float2*>(fp + 16 * i + 8);
        fr[i][0] = pack_bf16(rbf(p.x - mb) * rinv, rbf(p.y - mb) * rinv);
        fr[i][1] = pack_bf16(rbf(q.x - mb) * rinv, rbf(q.y - mb) * rinv);
    }
}

__device__ __forceinline__ void ln_rows2(const float (&v)[2][3], float* hrow2, float4* stats, int hw, int lane, uint32_t (&fr)[5][2]) {
    const int g = lane >> 2, j = lane & 3;
    const bool full = j < 3;
    float* hp = hrow2 + 80 * hw + 24 * j + g;
    hp[0] = v[0][0]; hp[DM] = v[1][0];
    if (full) { hp[8] = v[0][1]; hp[16] = v[0][2]; hp[DM + 8] = v[1][1]; hp[DM + 16] = v[1][2]; }
    float c[2], s1[2], s2[2];
#pragma unroll
    for (int r = 0; r < 2; r++) {
        c[r] = __shfl_sync(0xffffffffu, v[r][0], 0);
        const float d0 = v[r][0] - c[r], d1 = full ? v[r][1] - c[r] : 0.f, d2 = full ? v[r][2] - c[r] : 0.f;
        s1[r] = d0 + d1 + d2; s2[r] = d0 * d0 + d1 * d1 + d2 * d2;
    }
#pragma unroll
    for (int o = 16; o >= 1; o >>= 1) {
#pragma unroll
        for (int r = 0; r < 2; r++) { s1[r] += __shfl_xor_sync(0xffffffffu, s1[r], o); s2[r] += __shfl_xor_sync(0xffffffffu, s2[r], o); }
    }
    if (lane == 0) stats[hw] = make_float4(c[0] + s1[0] * (1.0f / 80.0f), s2[0] - s1[0] * s1[0] * (1.0f / 80.0f),
                                           c[1] + s1[1] * (1.0f / 80.0f), s2[1] - s1[1] * s1[1] * (1.0f / 80.0f));
    named_bar(2, NHELP_WARPS * 32);
    const int row = g & 1;
    const float2* sp = reinterpret_cast<const float2*>(stats) + row;
    float mw[8], m2 = 0.f, mean = 0.f;
#pragma unroll
    for (int k = 0; k < 8; k++) { const float2 t = sp[2 * k]; mw[k] = t.x; mean += t.x; m2 += t.y; }
    mean *= 0.125f;
    float dev = 0.f;
#pragma unroll
    for (int k = 0; k < 8; k++) dev += (mw[k] - mean) * (mw[k] - mean);
    const float mb = rbf(mean);
    const float rinv = __frcp_rn(rbf(__fsqrt_rn(rbf(rbf(fmaxf(m2 + 80.0f * dev, 0.f) * (1.0f / DM)) + LN_EPS))));
    const float* fp = hrow2 + row * DM + 80 * hw + 2 * j;
#pragma unroll
    for (int i = 0; i < 5; i++) {
        const float2 p = *reinterpret_cast<const float2*>(fp + 16 * i);
        const float2 q = *reinterpret_cast<const float2*>(fp + 16 * i + 8);
        fr[i][0] = (g < 2) ? pack_bf16(rbf(p.x - mb) * rinv, rbf(p.y - mb) * rinv) : 0u;
        fr[i][1] = (g < 2) ? pack_bf16(rbf(q.x - mb) * rinv, rbf(q.y - mb) * rinv) : 0u;
    }
}

__global__ void __launch_bounds__(NTHREADS, 1)
fused_decode_kernel(const __grid_constant__ CUtensorMap tmK, const __grid_constant__ CUtensorMap tmV,
                    const __grid_constant__ CUtensorMap tmWo,
                    const __grid_constant__ CUtensorMap tmW1, const __grid_constant__ CUtensorMap tmW2,
                    const __nv_bfloat16* __restrict__ x, const __nv_bfloat16* __restrict__ wq, __nv_bfloat16* __restrict__ out)
{
    extern __shared__ __align__(1024) unsigned char smem[];
    const uint32_t sbase = smem_u32(smem);
    const int tid = threadIdx.x, warp = tid >> 5, lane = tid & 31;
    const int cta = blockIdx.x, G = gridDim.x;

    const uint32_t bar_full = sbase + OFF_BARS;
    const uint32_t bar_empty = bar_full + NSX * 8;
    const uint32_t bar_wo = bar_empty + NSX * 8;
    const int lim0 = (USE_EXTRA && cta >= XCTA) ? NSX : NS;
    const uint32_t bar_w1 = bar_wo + 8;
    const uint32_t bar_w2 = bar_w1 + 8;
    const uint32_t bar_cdone = bar_w2 + 8;
    volatile int* meta = reinterpret_cast<volatile int*>(smem + OFF_META);

    uint64_t pol = 0;
    const int ht = tid - NCONS_WARPS * 32;
    auto load_wq = [&]() {
        const __nv_bfloat16* src = wq + cta * 48;
#pragma unroll
        for (int i = 0; i < 15; i++) {
            const int idx = ht + 256 * i, row = idx / 6, u = idx - 6 * row;
            cp_async16(sbase + OFF_WQO + idx * 16, src + (size_t)row * (NH * DH) + u * 8);
        }
        asm volatile("cp.async.commit_group;" ::: "memory");
    };
    if (warp >= NCONS_WARPS && warp < NCONS_WARPS + NHELP_WARPS && cta < NROLE) {
        if (ht < 160) cp_async16(sbase + OFF_HROW + ht * 16, x + ht * 8);
        if (ht == 160) cp_async16(sbase + OFF_EPOCH, &g_epoch);
        asm volatile("cp.async.commit_group;" ::: "memory");
        if (cta < 4 * LEAD) load_wq();
    }
    if (warp == NCONS_WARPS + NHELP_WARPS && lane == 0) {
        PROF(0);
        for (int i = 0; i < NSX; i++) { mbar_init(bar_full + 8 * i, 1); mbar_init(bar_empty + 8 * i, NCONS_WARPS); }
        mbar_init(bar_wo, 1); mbar_init(bar_w1, 1); mbar_init(bar_w2, 1); mbar_init(bar_cdone, NCONS_WARPS);
        asm volatile("fence.mbarrier_init.release.cluster;" ::: "memory");
        asm volatile("fence.proxy.async.shared::cta;" ::: "memory");
        asm volatile("createpolicy.fractional.L2::evict_first.b64 %0, 1.0;" : "=l"(pol));
        if (START_DELAY > 0) { const long long t0 = clock64(); while (clock64() - t0 < START_DELAY) { } }
        meta[0] = cta;
        mbar_expect_tx(bar_full, TILE_BYTES);
        tma2d_hint(sbase + OFF_RING, &tmK, 0, cta * 192, bar_full, pol);
        mbar_expect_tx(bar_full + 8, TILE_BYTES);
        tma2d_hint(sbase + OFF_RING + TILE_BYTES, &tmV, 0, cta * 192, bar_full + 8, pol);
    }
    __syncthreads();

    if (warp == NCONS_WARPS + NHELP_WARPS) {
        asm volatile("setmaxnreg.dec.sync.aligned.u32 40;");
        if (lane == 0) {
            unsigned long long old = atomicAdd(&g_claim.v, 1ULL);
            PROF_REF();
            int slot = 2, lim = lim0; uint32_t ph = 1;
            int wslot = 0, wlim = lim0; uint32_t wph = 0;
            while (true) {
                const int unit = (int)(old & (NUNITS - 1)) + G;
                if (unit >= NUNITS) break;
                if (unit < NUNITS - ENDGAME) { mbar_wait(bar_full + 8 * wslot, wph); if (++wslot == wlim) { wslot = 0; wph ^= 1; wlim = NS; } }
                mbar_wait(bar_empty + 8 * slot, ph);
                meta[slot] = unit;
                mbar_expect_tx(bar_full + 8 * slot, TILE_BYTES);
                tma2d_hint(sbase + OFF_RING + slot * TILE_BYTES, &tmK, 0, unit * 192, bar_full + 8 * slot, pol);
                if (++slot == lim) { slot = 0; ph ^= 1; lim = NS; }
                if (unit < NUNITS - ENDGAME) { mbar_wait(bar_full + 8 * wslot, wph); if (++wslot == wlim) { wslot = 0; wph ^= 1; wlim = NS; } }
                mbar_wait(bar_empty + 8 * slot, ph);
                mbar_expect_tx(bar_full + 8 * slot, TILE_BYTES);
                tma2d_hint(sbase + OFF_RING + slot * TILE_BYTES, &tmV, 0, unit * 192, bar_full + 8 * slot, pol);
                if (++slot == lim) { slot = 0; ph ^= 1; lim = NS; }
                old = atomicAdd(&g_claim.v, 1ULL);
            }
            PROF(2);
            PROF_REF2();
            mbar_wait(bar_empty + 8 * slot, ph);
            meta[slot] = -1;
            mbar_arrive(bar_full + 8 * slot);
            if (lim == NSX) {
                for (int s2 = max(slot, NS); s2 < NSX; s2++)
                    for (int k = 0; k < NCONS_WARPS; k++) mbar_arrive(bar_empty + 8 * s2);
            }
        }
    } else if (warp < NCONS_WARPS) {
        asm volatile("setmaxnreg.dec.sync.aligned.u32 96;");
        const int w = warp, g = lane >> 2, j = lane & 3;
        uint4* const dat_base = g_dat + ((size_t)w * 8 + g) * MAXG + cta;
        uint4* const hdr_base = g_hdr + cta;
        const uint32_t epoch = ld_relaxed_u32(&g_epoch.v);
        const uint32_t flag = epoch + 1u;
        uint32_t koff[3];
        {
            const int key = 16 * w + (lane & 7) + 8 * ((lane >> 3) & 1), hi = lane >> 4;
#pragma unroll
            for (int c = 0; c < 3; c++) { const int r = key * 3 + c; koff[c] = r * 128 + (((r & 7) ^ hi) << 4); }
        }
        uint32_t voff[3];
        {
            const int key = (lane & 7) + 8 * (lane >> 4), hi = (lane >> 3) & 1;
#pragma unroll
            for (int mt = 0; mt < 3; mt++) {
                const int U = 6 * w + 2 * mt + hi, c = U >> 3, u = U & 7, r = key * 3 + c;
                voff[mt] = r * 128 + ((u ^ (r & 7)) << 4);
            }
        }
        const bool act = (g >> 1) == j;
        const uint32_t sel0 = act ? ((g & 1) ? 0x1044u : 0x4410u) : 0x4444u;
        const uint32_t sel1 = act ? ((g & 1) ? 0x3244u : 0x4432u) : 0x4444u;
        float* sbuf = reinterpret_cast<float*>(smem + OFF_SBUF);
        const uint32_t qraw = sbase + OFF_QRAW + w * 512;

        uint32_t qf[24];
        float o[3][4];
        float m_run = -INFINITY, l_run = 0.f;
        int cur_bh = -1, pre_bh = -1, done_bh = -1, par = 0;
        const uint32_t dnraw = sbase + OFF_DONE + w * 16;
        int slot = 0, lim = lim0; uint32_t ph = 0;

        auto advance_to = [&](int nb) {
#pragma unroll 1
            while (cur_bh < nb) {
                if (cur_bh >= 0 && !EXP_NOFLUSH) {
                    if (cur_bh >= PSLOTS && !EXP_NOMERGE) {
                        uint4 dn = lds128(dnraw);
                        if (done_bh != cur_bh - PSLOTS || dn.x != flag || dn.y != flag || dn.z != flag || dn.w != flag) {
                            const long long t0 = clock64();
                            do { dn = ld_ll(g_done + cur_bh - PSLOTS); spin_check(t0); } while (dn.x != flag || dn.y != flag || dn.z != flag || dn.w != flag);
                        }
                    }
                    const uint32_t tag = flag * 8u + (uint32_t)(cur_bh >> 3);
                    float lo[3], hi[3];
#pragma unroll
                    for (int mt = 0; mt < 3; mt++) {
                        lo[mt] = o[mt][0] + o[mt][1]; hi[mt] = o[mt][2] + o[mt][3];
                        lo[mt] += __shfl_xor_sync(0xffffffffu, lo[mt], 1); hi[mt] += __shfl_xor_sync(0xffffffffu, hi[mt], 1);
                        lo[mt] += __shfl_xor_sync(0xffffffffu, lo[mt], 2); hi[mt] += __shfl_xor_sync(0xffffffffu, hi[mt], 2);
                    }
                    if (j == 0)
                        st_ll(dat_base + (cur_bh & (PSLOTS - 1)) * (4 * 8 * MAXG), pack_bf16(lo[0], hi[0]), pack_bf16(lo[1], hi[1]), pack_bf16(lo[2], hi[2]), tag);
                    if (w == 0) {
                        float l = l_run;
                        l += __shfl_xor_sync(0xffffffffu, l, 4);
                        l += __shfl_xor_sync(0xffffffffu, l, 8);
                        l += __shfl_xor_sync(0xffffffffu, l, 16);
                        if (lane == 1) st_ll(hdr_base + (cur_bh & (PSLOTS - 1)) * MAXG, __float_as_uint(m_run), __float_as_uint(l), 0u, tag);
                    }
                }
                m_run = -INFINITY; l_run = 0.f;
#pragma unroll
                for (int mt = 0; mt < 3; mt++) { o[mt][0] = o[mt][1] = o[mt][2] = o[mt][3] = 0.f; }
                cur_bh++;
            }
        };

        {
            if (w == 0) {
                const long long t0 = clock64();
                const uint4* qp = g_qll + lane;
                uint4 r0 = ld_ll(qp), r1, r2;
                const uint32_t fl = flag;
                __nanosleep(QPOLL_NS); r1 = ld_ll(qp);
                __nanosleep(QPOLL_NS); r2 = ld_ll(qp);
                while (true) {
                    if (__all_sync(0xffffffffu, r0.w == fl)) break;
                    r0 = ld_ll(qp); __nanosleep(QPOLL_NS);
                    if (__all_sync(0xffffffffu, r1.w == fl)) { r0 = r1; break; }
                    r1 = ld_ll(qp); __nanosleep(QPOLL_NS);
                    if (__all_sync(0xffffffffu, r2.w == fl)) { r0 = r2; break; }
                    r2 = ld_ll(qp); __nanosleep(QPOLL_NS);
                    spin_check(t0);
                }
#pragma unroll
                for (int k = 0; k < NCONS_WARPS; k++)
                    asm volatile("st.shared.v4.u32 [%0], {%1,%2,%3,%4};" :: "r"(sbase + OFF_QRAW + k * 512 + lane * 16), "r"(r0.x), "r"(r0.y), "r"(r0.z), "r"(r0.w) : "memory");
            }
            named_bar(1, NCONS_WARPS * 32);
            pre_bh = 0;
        }

        while (true) {
            mbar_wait(bar_full + 8 * slot, ph);
            const int unit = meta[slot];
            if (unit < 0) break;
            const int bh = unit >> 8;
            if (bh != cur_bh) {
                if (w == 0 && lane == 0 && cur_bh < 0) PROF(24);
                cp_async_wait_all();
                __syncwarp();
                advance_to(bh);
                bool have = false;
                if (pre_bh == bh) {
                    bool ok = true;
#pragma unroll
                    for (int t = 0; t < 8; t++) {
                        const uint4 r = lds128(qraw + (j * 8 + t) * 16);
                        qf[3 * t] = r.x; qf[3 * t + 1] = r.y; qf[3 * t + 2] = r.z;
                        ok = ok && (r.w == flag);
                    }
                    have = __all_sync(0xffffffffu, ok);
                }
                if (!have) {
                    const long long t0 = clock64();
                    const uint4* qp = g_qll + bh * 32 + lane;
                    uint4 r0 = ld_ll(qp);
                    while (!__all_sync(0xffffffffu, r0.w == flag)) { __nanosleep(200); r0 = ld_ll(qp); spin_check(t0); }
                    asm volatile("st.shared.v4.u32 [%0], {%1,%2,%3,%4};" :: "r"(qraw + lane * 16), "r"(r0.x), "r"(r0.y), "r"(r0.z), "r"(r0.w) : "memory");
                    __syncwarp();
#pragma unroll
                    for (int t = 0; t < 8; t++) {
                        const uint4 r = lds128(qraw + (j * 8 + t) * 16);
                        qf[3 * t] = r.x; qf[3 * t + 1] = r.y; qf[3 * t + 2] = r.z;
                    }
                }
                __syncwarp();
                if (w == 0 && lane == 0 && bh == 0) PROF(1);
                pre_bh = bh + 1;
                if (pre_bh < NBH) cp_async16(qraw + lane * 16, g_qll + pre_bh * 32 + lane);
                done_bh = bh - PSLOTS;
                if (done_bh >= 0 && lane == 0) cp_async16(dnraw, g_done + done_bh);
            }
            float s0[4] = {0.f, 0.f, 0.f, 0.f}, s1[4] = {0.f, 0.f, 0.f, 0.f}, s2[4] = {0.f, 0.f, 0.f, 0.f};
            {
                const uint32_t kb = sbase + OFF_RING + slot * TILE_BYTES;
#pragma unroll
                for (int i = 0; i < 4; i++) {
                    uint32_t a[4], b[4], c[4];
                    ldsm4(a, kb + (koff[0] ^ (i * 32)));
                    ldsm4(b, kb + (koff[1] ^ (i * 32)));
                    ldsm4(c, kb + (koff[2] ^ (i * 32)));
                    mma16816(s0, a, qf[2 * i], qf[2 * i + 1]);
                    mma16816(s1, b, qf[8 + 2 * i], qf[8 + 2 * i + 1]);
                    mma16816(s2, c, qf[16 + 2 * i], qf[16 + 2 * i + 1]);
                }
            }
            const float slo = rbf(rbf(s0[0] + s1[0] + s2[0]) * SM_SCALE), shi = rbf(rbf(s0[2] + s1[2] + s2[2]) * SM_SCALE);
            __syncwarp();
            if (lane == 0) mbar_arrive(bar_empty + 8 * slot);
            if (++slot == lim) { slot = 0; ph ^= 1; lim = NS; }
            float* sb = sbuf + par * 64;
            if (j == 0) { sb[16 * w + g] = slo; sb[16 * w + 8 + g] = shi; }
            par ^= 1;
            named_bar(1, NCONS_WARPS * 32);
            float sv[8];
#pragma unroll
            for (int kk = 0; kk < 4; kk++) { sv[2 * kk] = sb[16 * kk + g]; sv[2 * kk + 1] = sb[16 * kk + 8 + g]; }
            float mx = fmaxf(fmaxf(fmaxf(sv[0], sv[1]), fmaxf(sv[2], sv[3])), fmaxf(fmaxf(sv[4], sv[5]), fmaxf(sv[6], sv[7])));
            mx = warp_max(mx);
            const float m_new = fmaxf(m_run, mx);
            const float mc = m_new * LOG2E;
            const float alpha = ex2(m_run * LOG2E - mc);
            m_run = m_new;
            uint32_t pb[4][2];
            float psum = 0.f;
#pragma unroll
            for (int kk = 0; kk < 4; kk++) {
                const float p0 = ex2(fmaf(sv[2 * kk], LOG2E, -mc));
                const float p1 = ex2(fmaf(sv[2 * kk + 1], LOG2E, -mc));
                psum += p0 + p1;
                const uint32_t pk = pack_bf16(p0, p1);
                pb[kk][0] = __byte_perm(pk, 0u, sel0);
                pb[kk][1] = __byte_perm(pk, 0u, sel1);
            }
            l_run = l_run * alpha + psum;
#pragma unroll
            for (int mt = 0; mt < 3; mt++) { o[mt][0] *= alpha; o[mt][1] *= alpha; o[mt][2] *= alpha; o[mt][3] *= alpha; }
            mbar_wait(bar_full + 8 * slot, ph);
            {
                const uint32_t vb = sbase + OFF_RING + slot * TILE_BYTES;
#pragma unroll
                for (int k2 = 0; k2 < 4; k2 += 2) {
                    uint32_t a[2][3][4];
#pragma unroll
                    for (int kk = 0; kk < 2; kk++)
#pragma unroll
                        for (int mt = 0; mt < 3; mt++) ldsm4t(a[kk][mt], vb + voff[mt] + (k2 + kk) * 6144);
#pragma unroll
                    for (int kk = 0; kk < 2; kk++)
#pragma unroll
                        for (int mt = 0; mt < 3; mt++) mma16816(o[mt], a[kk][mt], pb[k2 + kk][0], pb[k2 + kk][1]);
                }
            }
            __syncwarp();
            if (lane == 0) mbar_arrive(bar_empty + 8 * slot);
            if (++slot == lim) { slot = 0; ph ^= 1; lim = NS; }
        }
        cp_async_wait_all();
        __syncwarp();
        advance_to(NBH);
        if (lane == 0) mbar_arrive(bar_cdone);
        if (w == 0 && lane == 0) {
            PROF(3);
        }
        __syncwarp();
        if (cta == 0 && w == 0 && lane == 0 && EXP_NOMERGE) g_epoch.v = epoch + 1u;
        if (cta < NFIN && !EXP_NOMERGE) {
            TPDECL(4);
            const int nn = lane & 7, sub = lane >> 3;
            const int n = 8 * cta + nn;
            const long long t0 = clock64();
            float* fred = reinterpret_cast<float*>(smem + OFF_FRED);
            const int hw2 = n / 80, r = n - 80 * hw2, idx = r >> 3, jj = idx / 3, tt = idx - 3 * jj;
            const int yoff = sub * 256 + hw2 * 32 + nn * 4 + jj;
            const uint4* zp = g_z + (size_t)(24 * w + sub) * DM + n;
            float xb = 0.f, abase = 0.f, yv = 0.f;
#pragma unroll 1
            for (int pass = 0; pass < 2; pass++) {
                if (pass) {
                    if (w == 0) {
                        if (lane == 0) wait_counter(&g_ycnt.v, flag * YCNT, 200);
                        __syncwarp();
                        if (lane < 16) { xb = __bfloat162float(x[sub * DM + n]); abase = ld_relaxed_f32(g_hacc[epoch & 1] + sub * DM + n); }
                    }
                    if (w < NDIRECT - 1) {
                        const uint4* yp = g_y + w * 1024 + yoff;
                        uint4 d = ld_ll(yp);
                        while (d.w != flag) { __nanosleep(100); d = ld_ll(yp); spin_check(t0); }
                        yv = __uint_as_float(tt == 0 ? d.x : (tt == 1 ? d.y : d.z));
                    }
                    const uint4* yp = g_y + (NDIRECT - 1) * 1024 + yoff;
                    uint4 d = ld_ll(yp);
                    while (d.w != flag) { d = ld_ll(yp); spin_check(t0); }
                    if (w == NDIRECT - 1) yv = __uint_as_float(tt == 0 ? d.x : (tt == 1 ? d.y : d.z));
                    __syncwarp();
                    TP(0);
                    const long long t1 = clock64();
                    while (clock64() - t1 < ZWAIT) { }
                }
                uint4 d[6];
#pragma unroll
                for (int s = 0; s < 6; s++) d[s] = ld_ll(zp + (size_t)4 * s * DM);
                if (pass) {
                    while (true) {
                        bool ok = true;
#pragma unroll
                        for (int s = 0; s < 6; s++) { if (d[s].w != flag) { ok = false; d[s] = ld_ll(zp + (size_t)4 * s * DM); } }
                        if (ok) break;
                        spin_check(t0);
                    }
                }
                float z0 = 0.f, z1 = 0.f, ya = yv;
#pragma unroll
                for (int s = 0; s < 6; s++) { z0 += __uint_as_float(d[s].x); z1 += __uint_as_float(d[s].y); }
                __syncwarp();
                TP(1);
                z0 += __shfl_xor_sync(0xffffffffu, z0, 8); z1 += __shfl_xor_sync(0xffffffffu, z1, 8); ya += __shfl_xor_sync(0xffffffffu, ya, 8);
                z0 += __shfl_xor_sync(0xffffffffu, z0, 16); z1 += __shfl_xor_sync(0xffffffffu, z1, 16); ya += __shfl_xor_sync(0xffffffffu, ya, 16);
                if (lane < 8) { fred[w * 24 + nn] = z0; fred[w * 24 + 8 + nn] = z1; fred[w * 24 + 16 + nn] = ya; }
                named_bar(1, NCONS_WARPS * 32);
                if (w == 0 && lane < 16) {
                    const float mlp = (fred[lane] + fred[24 + lane]) + (fred[48 + lane] + fred[72 + lane]);
                    const float yd = (fred[16 + nn] + fred[40 + nn]) + (fred[64 + nn] + fred[88 + nn]);
                    const float h = rbf(xb + rbf(abase + (sub ? yd : 0.f)));
                    if (pass) out[sub * DM + n] = __float2bfloat16(h + rbf(mlp));
                }
                if (!pass) named_bar(1, NCONS_WARPS * 32);
            }
            TP(2);
            if (cta == 0 && w == 0 && lane == 0) g_epoch.v = epoch + 1u;
            if (w == 0 && lane == 0) { TPOUT(13, 0); TPOUT(14, 1); TPOUT(7, 2); }
        }
    } else {
        asm volatile("setmaxnreg.inc.sync.aligned.u32 144;");
        if (cta >= NROLE) return;
        const int hw = warp - NCONS_WARPS;
        const int g = lane >> 2, j = lane & 3;
        const int head = cta >> 2, qd = cta & 3;
        int own[3];
#pragma unroll
        for (int t = 0; t < 3; t++) { const int idx = (j < 3) ? 3 * j + t : 9; own[t] = 80 * hw + 16 * (idx >> 1) + 8 * (idx & 1) + g; }
        if (ht < 16) st_ll(g_qll + ((ht >> 3) * NH + head) * 32 + ((ht >> 1) & 3) * 8 + 2 * qd + (ht & 1), 0u, 0u, 0u, 0u);
        float xv[2][3];
        {
            if (cta < 4 * LEAD) asm volatile("cp.async.wait_group 1;" ::: "memory"); else asm volatile("cp.async.wait_group 0;" ::: "memory");
            named_bar(2, NHELP_WARPS * 32);
            if (ht == 0) PROF(23);
            const __nv_bfloat16* xs = reinterpret_cast<const __nv_bfloat16*>(smem + OFF_HROW);
#pragma unroll
            for (int t = 0; t < 3; t++) { xv[0][t] = __bfloat162float(xs[own[t]]); xv[1][t] = __bfloat162float(xs[DM + own[t]]); }
        }
        const uint32_t epoch = *reinterpret_cast<const uint32_t*>(smem + OFF_EPOCH);
        const uint32_t flag = epoch + 1u;
        float* hacc = g_hacc[epoch & 1];
        float* hrow = reinterpret_cast<float*>(smem + OFF_HROW);
        float2* stats = reinterpret_cast<float2*>(smem + OFF_STATS);
        const int krow = (lane & 7) + 8 * (lane >> 4), mhi = (lane >> 3) & 1;
        const long long tstart = clock64();
        auto wait_claims = [&](int target) {
            while (true) {
                const int rem = target - (int)(ld_relaxed_u64(&g_claim.v) - ((unsigned long long)epoch << 14));
                if (rem <= 0) break;
                const unsigned ns = rem > 2000 ? 8000u : (unsigned)rem * 4u;
                __nanosleep(ns < 64u ? 64u : ns);
                spin_check(tstart);
            }
        };
        TPDECL(12);
        auto load_w12 = [&]() {
            mbar_expect_tx(bar_w1, 20480);
#pragma unroll
            for (int i = 0; i < 5; i++) tma2d(sbase + OFF_W1 + i * 4096, &tmW1, cta * 16, i * 128, bar_w1);
            mbar_expect_tx(bar_w2, 20480);
            tma3d(sbase + OFF_W2, &tmW2, 0, 0, cta * 16, bar_w2);
        };

        {
            if (cta >= 4 * LEAD) {
                if (ht == 0) wait_claims((head - LEAD) * TPB - G);
                if (USE_EXTRA && cta >= XCTA) {
#pragma unroll
                    for (int i = NS; i < NSX; i++) mbar_wait(bar_empty + 8 * i, 0);
                }
                named_bar(2, NHELP_WARPS * 32);
                if (!(EXP_SKIP & 4)) load_wq();
            }
            uint32_t bf[5][2];
            ln_rows2(xv, reinterpret_cast<float*>(smem + OFF_W1), reinterpret_cast<float4*>(smem + OFF_STATS), hw, lane, bf);
            if (ht == 0) PROF(8);
            cp_async_wait_all();
            named_bar(2, NHELP_WARPS * 32);
            if (ht == 0) PROF(9);
            float* red = reinterpret_cast<float*>(smem + OFF_RED_Q);
            float acc[3][4];
#pragma unroll
            for (int mt = 0; mt < 3; mt++) { acc[mt][0] = acc[mt][1] = acc[mt][2] = acc[mt][3] = 0.f; }
#pragma unroll
            for (int i = 0; i < 5; i++) {
                const uint32_t rowaddr = sbase + OFF_WQO + (16 * (5 * hw + i) + krow) * 96 + mhi * 16;
#pragma unroll
                for (int mt = 0; mt < 3; mt++) {
                    uint32_t a[4];
                    ldsm4t(a, rowaddr + mt * 32);
                    mma16816(acc[mt], a, bf[i][0], bf[i][1]);
                }
            }
            if (j == 0) {
#pragma unroll
                for (int mt = 0; mt < 3; mt++) {
                    red[hw * 96 + 16 * mt + g] = acc[mt][0];
                    red[hw * 96 + 48 + 16 * mt + g] = acc[mt][1];
                    red[hw * 96 + 16 * mt + 8 + g] = acc[mt][2];
                    red[hw * 96 + 48 + 16 * mt + 8 + g] = acc[mt][3];
                }
            }
            named_bar(2, NHELP_WARPS * 32);
            if (ht < 96) {
                float s = 0.f;
#pragma unroll
                for (int k = 0; k < 8; k++) s += red[k * 96 + ht];
                red[8 * 96 + ht] = s;
            }
            named_bar(2, NHELP_WARPS * 32);
            if (ht < 16) {
                const int b = ht >> 3, jj = (ht >> 1) & 3, e2 = ht & 1;
                uint32_t fw[3];
#pragma unroll
                for (int r = 0; r < 3; r++) {
                    const int rl = 3 * e2 + r;
                    const int col = 16 * (rl >> 1) + 8 * (rl & 1) + 2 * jj;
                    fw[r] = pack_bf16(red[8 * 96 + b * 48 + col], red[8 * 96 + b * 48 + col + 1]);
                }
                st_ll(g_qll + (b * NH + head) * 32 + jj * 8 + 2 * qd + e2, fw[0], fw[1], fw[2], flag);
            }
            __syncwarp();
            named_bar(2, NHELP_WARPS * 32);
            if (ht == 0) {
                PROF(10);
                asm volatile("fence.proxy.async;" ::: "memory");
                if (!(EXP_SKIP & 1)) {
                mbar_expect_tx(bar_wo, 61440);
                tma3d(sbase + OFF_WQO, &tmWo, 0, 0, cta * 48, bar_wo);
                }
                if (cta < NMLP && W12_AT == 0 && !(EXP_SKIP & 2)) load_w12();
            }
            if (head >= NH - NDIRECT) st_ll(g_y + ((head - (NH - NDIRECT)) * 4 + qd) * 256 + ht, 0u, 0u, 0u, 0u);
            if (cta < NMLP) {
#pragma unroll
                for (int i = 0; i < 3; i++) if (ht + 256 * i < DM) st_ll(g_z + (size_t)cta * DM + ht + 256 * i, 0u, 0u, 0u, 0u);
            }
            if (cta == 0) {
#pragma unroll
                for (int i = 0; i < 5; i++) g_hacc[(epoch + 1) & 1][ht + 256 * i] = 0.f;
            }
        }

        if (EXP_NOMERGE) return;
        __nv_bfloat16* obf = reinterpret_cast<__nv_bfloat16*>(smem + OFF_OBF);
        uint32_t wof[3][5][4];
        mbar_wait(bar_wo, 0);
#pragma unroll
        for (int i = 0; i < 5; i++) {
            const int mt = 5 * hw + i;
#pragma unroll
            for (int ks = 0; ks < 3; ks++) {
                const int line = (16 * ks + krow) * 10 + (mt >> 2);
                ldsm4t(wof[ks][i], sbase + OFF_WQO + line * 128 + (((2 * (mt & 3) + mhi) ^ (line & 7)) << 4));
            }
        }
#pragma unroll 1
        for (int b = 0; b < NB; b++) {
            const int bh = b * NH + head;
            const bool last = (bh == NBH - 1), direct = (bh >= NBH - NDIRECT);
            uint4 hd[5], dt[5];
            const uint32_t tag = flag * 8u + (uint32_t)(bh >> 3);
#pragma unroll 1
            for (int pass = last ? 0 : 1; pass < 2; pass++) {
                if (pass) {
                    if (last) mbar_wait(bar_cdone, 0);
                    else {
                        if (ht == 0) wait_claims(min((bh + 1) * TPB + (direct ? 1 : MERGE_MARGIN) * G, NUNITS - G));
                        named_bar(2, NHELP_WARPS * 32);
                    }
                } else {
                    if (ht == 0) wait_claims(NUNITS - G - 400);
                    named_bar(2, NHELP_WARPS * 32);
                }
                const uint32_t pend = pass ? tag - 1u : tag;
#pragma unroll
                for (int s = 0; s < 5; s++) {
                    const uint32_t st = (lane + 32 * s < G) ? pend : tag;
                    hd[s] = make_uint4(0xff800000u, 0u, 0u, st); dt[s] = make_uint4(0u, 0u, 0u, st);
                }
                {
                    const uint4* hp = g_hdr + (bh & (PSLOTS - 1)) * MAXG + lane;
                    const uint4* dp = g_dat + (((bh & (PSLOTS - 1)) * 4 + qd) * 8 + hw) * MAXG + lane;
                    while (true) {
#pragma unroll
                        for (int s = 0; s < 5; s++) {
                            if (dt[s].w != tag) dt[s] = ld_ll(dp + 32 * s);
                            if (hd[s].w != tag) hd[s] = ld_ll(hp + 32 * s);
                        }
                        bool ok = true;
#pragma unroll
                        for (int s = 0; s < 5; s++) ok = ok && dt[s].w == tag && hd[s].w == tag;
                        if (__all_sync(0xffffffffu, ok)) break;
                        if (!last) __nanosleep(direct ? 250 : 500);
                        spin_check(tstart);
                    }
                }
                TP(6);
                const float M = warp_max(fmaxf(fmaxf(fmaxf(__uint_as_float(hd[0].x), __uint_as_float(hd[1].x)),
                                               fmaxf(__uint_as_float(hd[2].x), __uint_as_float(hd[3].x))), __uint_as_float(hd[4].x)));
                float a[8];
#pragma unroll
                for (int i = 0; i < 8; i++) a[i] = 0.f;
#pragma unroll
                for (int s = 0; s < 5; s++) {
                    const float wgt = ex2((__uint_as_float(hd[s].x) - M) * LOG2E);
                    a[0] = fmaf(wgt, __uint_as_float(dt[s].x << 16), a[0]);
                    a[1] = fmaf(wgt, __uint_as_float(dt[s].x & 0xffff0000u), a[1]);
                    a[2] = fmaf(wgt, __uint_as_float(dt[s].y << 16), a[2]);
                    a[3] = fmaf(wgt, __uint_as_float(dt[s].y & 0xffff0000u), a[3]);
                    a[4] = fmaf(wgt, __uint_as_float(dt[s].z << 16), a[4]);
                    a[5] = fmaf(wgt, __uint_as_float(dt[s].z & 0xffff0000u), a[5]);
                    a[6] = fmaf(wgt, __uint_as_float(hd[s].y), a[6]);
                }
                {
                    const bool up16 = lane & 16, up8 = lane & 8, up4 = lane & 4;
#pragma unroll
                    for (int i = 0; i < 4; i++) a[i] = (up16 ? a[i + 4] : a[i]) + __shfl_xor_sync(0xffffffffu, up16 ? a[i] : a[i + 4], 16);
#pragma unroll
                    for (int i = 0; i < 2; i++) a[i] = (up8 ? a[i + 2] : a[i]) + __shfl_xor_sync(0xffffffffu, up8 ? a[i] : a[i + 2], 8);
                    a[0] = (up4 ? a[1] : a[0]) + __shfl_xor_sync(0xffffffffu, up4 ? a[0] : a[1], 4);
                    a[0] += __shfl_xor_sync(0xffffffffu, a[0], 2);
                    a[0] += __shfl_xor_sync(0xffffffffu, a[0], 1);
                    const float Lt = __shfl_sync(0xffffffffu, a[0], 24);
                    if (g < 6 && j == 0) obf[8 * g + hw] = __float2bfloat16(__fdividef(a[0], Lt));
                }
                named_bar(2, NHELP_WARPS * 32);
                TP(7);
                float yv[10];
                {
                    const uint32_t* ow = reinterpret_cast<const uint32_t*>(obf);
                    uint32_t bq[3][2];
#pragma unroll
                    for (int ks = 0; ks < 3; ks++) { bq[ks][0] = ow[8 * ks + j]; bq[ks][1] = ow[8 * ks + 4 + j]; }
                    float acc[5][4];
#pragma unroll
                    for (int i = 0; i < 5; i++) acc[i][0] = acc[i][1] = acc[i][2] = acc[i][3] = 0.f;
#pragma unroll
                    for (int ks = 0; ks < 3; ks++) {
#pragma unroll
                        for (int i = 0; i < 5; i++) mma16816(acc[i], wof[ks][i], bq[ks][0], bq[ks][1]);
                    }
#pragma unroll
                    for (int i = 0; i < 5; i++) { yv[2 * i] = acc[i][0]; yv[2 * i + 1] = acc[i][2]; }
                }
                const float y0 = j == 0 ? yv[0] : (j == 1 ? yv[3] : (j == 2 ? yv[6] : yv[9]));
                const float y1 = j == 0 ? yv[1] : (j == 1 ? yv[4] : yv[7]);
                const float y2 = j == 0 ? yv[2] : (j == 1 ? yv[5] : yv[8]);
                if (pass) {
                    if (direct) {
                        st_ll(g_y + ((bh - (NBH - NDIRECT)) * 4 + qd) * 256 + ht, __float_as_uint(y0), __float_as_uint(y1), __float_as_uint(y2), flag);
                    } else {
                        if (!(EXP2 & 1)) {
                        red_add_f32(hacc + b * DM + own[0], y0);
                        if (j < 3) { red_add_f32(hacc + b * DM + own[1], y1); red_add_f32(hacc + b * DM + own[2], y2); }
                        }
                    }
                }
                TP(8);
                named_bar(2, NHELP_WARPS * 32);
            }
            if (ht == 0) {
                if (!(EXP2 & 2)) fence_gpu();
                if (!direct) red_add_u32(&g_ycnt.v, 1u);
                asm volatile("st.relaxed.gpu.global.u32 [%0], %1;" :: "l"(reinterpret_cast<unsigned*>(g_done + bh) + qd), "r"(flag) : "memory");
            }
        }
        if (ht == 0) { TPOUT(11, 6); TPOUT(12, 7); TPOUT(4, 8); }
        if (cta >= NMLP) return;

        if (W12_AT != 0 && ht == 0) { wait_claims(NUNITS - G - W12_AT); load_w12(); }
        float hpre[3] = {0.f, 0.f, 0.f};
        uint32_t bf0[5][2], w1f[5][4], w2f[5][4];
#pragma unroll
        for (int i = 0; i < 5; i++) { bf0[i][0] = bf0[i][1] = 0u; }
        mbar_wait(bar_w1, 0);
#pragma unroll
        for (int i = 0; i < 5; i++) ldsm4t(w1f[i], sbase + OFF_W1 + (16 * (5 * hw + i) + krow) * 32 + mhi * 16);
        mbar_wait(bar_w2, 0);
#pragma unroll
        for (int i = 0; i < 5; i++) {
            const int mt = 5 * hw + i;
            const int line = krow * 10 + (mt >> 2);
            ldsm4t(w2f[i], sbase + OFF_W2 + line * 128 + (((2 * (mt & 3) + mhi) ^ (line & 7)) << 4));
        }
        float* red1 = reinterpret_cast<float*>(smem + OFF_RED1);
        uint4* const zout = g_z + (size_t)cta * DM + 80 * hw + g;
#pragma unroll 1
        for (int pass = 0; pass < 2; pass++) {
            if (pass) {
                if (ht == 0) { wait_claims((NBH - NDIRECT) * TPB - G); wait_counter(&g_ycnt.v, flag * YCNT, YSLEEP); }
                named_bar(2, NHELP_WARPS * 32);
                float h0[3];
#pragma unroll
                for (int t = 0; t < 3; t++) {
                    h0[t] = rbf(xv[0][t] + rbf(ld_relaxed_f32(hacc + own[t])));
                    hpre[t] = ld_relaxed_f32(hacc + DM + own[t]);
                }
                ln_row(h0, hrow, stats, hw, lane, bf0);
                TP(9);
#pragma unroll 1
                for (int dd = 0; dd < NDIRECT - 1; dd++) {
                    if (ht < 4) {
                        const uint4* yp = g_y + (dd * 4 + ht) * 256;
                        while (ld_ll(yp).w != flag) { __nanosleep(64); spin_check(tstart); }
                    }
                    named_bar(2, NHELP_WARPS * 32);
                    uint4 y[4];
                    const uint4* yp = g_y + dd * 1024 + ht;
#pragma unroll
                    for (int s = 0; s < 4; s++) y[s] = ld_ll(yp + s * 256);
#pragma unroll
                    for (int s = 0; s < 4; s++) {
                        while (y[s].w != flag) { y[s] = ld_ll(yp + s * 256); spin_check(tstart); }
                        hpre[0] += __uint_as_float(y[s].x); hpre[1] += __uint_as_float(y[s].y); hpre[2] += __uint_as_float(y[s].z);
                    }
                }
                TP(10);
                if (ht < 4) {
                    const uint4* yp = g_y + ((NDIRECT - 1) * 4 + ht) * 256;
                    while (ld_ll(yp).w != flag) spin_check(tstart);
                }
                named_bar(2, NHELP_WARPS * 32);
            }
            TP(0);
            uint4 y[4];
            const uint4* yp = g_y + (NDIRECT - 1) * 1024 + ht;
#pragma unroll
            for (int s = 0; s < 4; s++) y[s] = ld_ll(yp + s * 256);
            if (pass) {
                while (true) {
                    bool ok = true;
#pragma unroll
                    for (int s = 0; s < 4; s++) if (y[s].w != flag) { ok = false; y[s] = ld_ll(yp + s * 256); }
                    if (ok) break;
                    spin_check(tstart);
                }
            }
            float v[3];
            v[0] = rbf(xv[1][0] + rbf(hpre[0] + ((__uint_as_float(y[0].x) + __uint_as_float(y[1].x)) + (__uint_as_float(y[2].x) + __uint_as_float(y[3].x)))));
            v[1] = rbf(xv[1][1] + rbf(hpre[1] + ((__uint_as_float(y[0].y) + __uint_as_float(y[1].y)) + (__uint_as_float(y[2].y) + __uint_as_float(y[3].y)))));
            v[2] = rbf(xv[1][2] + rbf(hpre[2] + ((__uint_as_float(y[0].z) + __uint_as_float(y[1].z)) + (__uint_as_float(y[2].z) + __uint_as_float(y[3].z)))));
            TP(1);
            uint32_t fr[5][2];
            ln_row(v, hrow, stats + 8, hw, lane, fr);
            TP(2);
            float acc0[4] = {0.f, 0.f, 0.f, 0.f}, acc1[4] = {0.f, 0.f, 0.f, 0.f};
#pragma unroll
            for (int i = 0; i < 5; i++) {
                const uint32_t b0 = (g == 0) ? bf0[i][0] : ((g == 1) ? fr[i][0] : 0u);
                const uint32_t b1 = (g == 0) ? bf0[i][1] : ((g == 1) ? fr[i][1] : 0u);
                if (i & 1) mma16816(acc1, w1f[i], b0, b1); else mma16816(acc0, w1f[i], b0, b1);
            }
            if (j == 0) {
                red1[hw * 32 + g] = acc0[0] + acc1[0]; red1[hw * 32 + 16 + g] = acc0[1] + acc1[1];
                red1[hw * 32 + 8 + g] = acc0[2] + acc1[2]; red1[hw * 32 + 16 + 8 + g] = acc0[3] + acc1[3];
            }
            named_bar(2, NHELP_WARPS * 32);
            TP(3);
            uint32_t b0, b1;
            {
                const float* rp = red1 + (g & 1) * 16 + 2 * j;
                float2 p[8], q[8];
#pragma unroll
                for (int k = 0; k < 8; k++) { p[k] = *reinterpret_cast<const float2*>(rp + k * 32); q[k] = *reinterpret_cast<const float2*>(rp + k * 32 + 8); }
                const float lx = ((p[0].x + p[1].x) + (p[2].x + p[3].x)) + ((p[4].x + p[5].x) + (p[6].x + p[7].x));
                const float ly = ((p[0].y + p[1].y) + (p[2].y + p[3].y)) + ((p[4].y + p[5].y) + (p[6].y + p[7].y));
                const float hx = ((q[0].x + q[1].x) + (q[2].x + q[3].x)) + ((q[4].x + q[5].x) + (q[6].x + q[7].x));
                const float hy = ((q[0].y + q[1].y) + (q[2].y + q[3].y)) + ((q[4].y + q[5].y) + (q[6].y + q[7].y));
                b0 = pack_bf16(fmaxf(lx, 0.f), fmaxf(ly, 0.f));
                b1 = pack_bf16(fmaxf(hx, 0.f), fmaxf(hy, 0.f));
            }
            TP(4);
            float z[5][4];
#pragma unroll
            for (int i = 0; i < 5; i++) { z[i][0] = z[i][1] = z[i][2] = z[i][3] = 0.f; mma16816(z[i], w2f[i], b0, b1); }
            {
                const bool j1 = j & 1, j2 = j & 2;
                const float za0 = j2 ? (j1 ? z[1][2] : z[1][0]) : (j1 ? z[0][2] : z[0][0]), zb0 = j2 ? (j1 ? z[1][3] : z[1][1]) : (j1 ? z[0][3] : z[0][1]);
                const float za1 = j2 ? (j1 ? z[3][2] : z[3][0]) : (j1 ? z[2][2] : z[2][0]), zb1 = j2 ? (j1 ? z[3][3] : z[3][1]) : (j1 ? z[2][3] : z[2][1]);
                const float za2 = j1 ? z[4][2] : z[4][0], zb2 = j1 ? z[4][3] : z[4][1];
                if (pass) {
                    st_ll(zout + 8 * j, __float_as_uint(za0), __float_as_uint(zb0), 0u, flag);
                    st_ll(zout + 8 * (4 + j), __float_as_uint(za1), __float_as_uint(zb1), 0u, flag);
                    if (j < 2) st_ll(zout + 8 * (8 + j), __float_as_uint(za2), __float_as_uint(zb2), 0u, flag);
                }
            }
            TP(5);
            if (!pass) named_bar(2, NHELP_WARPS * 32);
        }
        if (ht == 0) { TPOUT(16, 0); TPOUT(17, 1); TPOUT(18, 2); TPOUT(19, 3); TPOUT(20, 4); TPOUT(21, 5); TPOUT(5, 9); TPOUT(6, 10); }
    }
}

typedef CUresult (*EncodeTiledFn)(CUtensorMap*, CUtensorMapDataType, cuuint32_t, void*, const cuuint64_t*, const cuuint64_t*,
                                  const cuuint32_t*, const cuuint32_t*, CUtensorMapInterleave, CUtensorMapSwizzle,
                                  CUtensorMapL2promotion, CUtensorMapFloatOOBfill);

static void make_map(EncodeTiledFn enc, CUtensorMap* tm, const void* base, uint64_t cols, uint64_t rows,
                     uint32_t box_cols, uint32_t box_rows, CUtensorMapSwizzle swz) {
    cuuint64_t dims[2] = {cols, rows};
    cuuint64_t strides[1] = {cols * 2};
    cuuint32_t box[2] = {box_cols, box_rows};
    cuuint32_t es[2] = {1, 1};
    enc(tm, CU_TENSOR_MAP_DATA_TYPE_BFLOAT16, 2, const_cast<void*>(base), dims, strides, box, es,
        CU_TENSOR_MAP_INTERLEAVE_NONE, swz, CU_TENSOR_MAP_L2_PROMOTION_NONE, CU_TENSOR_MAP_FLOAT_OOB_FILL_NONE);
}

static void make_map3(EncodeTiledFn enc, CUtensorMap* tm, const void* base, uint64_t rows, uint32_t box_rows) {
    cuuint64_t dims[3] = {64, 10, rows};
    cuuint64_t strides[2] = {128, DM * 2};
    cuuint32_t box[3] = {64, 10, box_rows};
    cuuint32_t es[3] = {1, 1, 1};
    enc(tm, CU_TENSOR_MAP_DATA_TYPE_BFLOAT16, 3, const_cast<void*>(base), dims, strides, box, es,
        CU_TENSOR_MAP_INTERLEAVE_NONE, CU_TENSOR_MAP_SWIZZLE_128B, CU_TENSOR_MAP_L2_PROMOTION_NONE, CU_TENSOR_MAP_FLOAT_OOB_FILL_NONE);
}

}

extern "C" void kernel_launch(void* const* d_in, const int* in_sizes, int n_in, void* d_out, int out_size) {
    using namespace fused;
    (void)in_sizes; (void)n_in; (void)out_size;
    static EncodeTiledFn enc = nullptr;
    static int grid = 0;
    if (!enc) {
        void* fn = nullptr;
        cudaDriverEntryPointQueryResult qr;
        cudaGetDriverEntryPoint("cuTensorMapEncodeTiled", &fn, cudaEnableDefault, &qr);
        enc = (EncodeTiledFn)fn;
        int dev = 0, sms = 0;
        cudaGetDevice(&dev);
        cudaDeviceGetAttribute(&sms, cudaDevAttrMultiProcessorCount, dev);
        grid = sms < MAXG ? sms : MAXG;
        cudaFuncSetAttribute(fused_decode_kernel, cudaFuncAttributeMaxDynamicSharedMemorySize, SMEM_BYTES);
    }
    const __nv_bfloat16* x = (const __nv_bfloat16*)d_in[0];
    CUtensorMap tmK, tmV, tmWo, tmW1, tmW2;
    make_map(enc, &tmK, d_in[1], 64, (uint64_t)NBH * SK * 3, 64, 192, CU_TENSOR_MAP_SWIZZLE_128B);
    make_map(enc, &tmV, d_in[2], 64, (uint64_t)NBH * SK * 3, 64, 192, CU_TENSOR_MAP_SWIZZLE_128B);
    make_map3(enc, &tmWo, d_in[4], NH * DH, 48);
    make_map(enc, &tmW1, d_in[6], DFF, DM, 16, 128, CU_TENSOR_MAP_SWIZZLE_NONE);
    make_map3(enc, &tmW2, d_in[7], DFF, 16);
    fused_decode_kernel<<<grid, NTHREADS, SMEM_BYTES>>>(tmK, tmV, tmWo, tmW1, tmW2, x, (const __nv_bfloat16*)d_in[3], (__nv_bfloat16*)d_out);
}
```

```cpp
#include <cuda_runtime.h>
#include <cuda_bf16.h>
#include <cuda.h>
#include <stdint.h>

namespace fused {

constexpr int NB = 2, DM = 640, NH = 32, SK = 16384, DH = 192, DFF = 1536;
constexpr int TILE = 64;
constexpr int TPB = SK / TILE;
constexpr int NBH = NB * NH;
constexpr int NUNITS = NBH * TPB;
constexpr int TILE_BYTES = TILE * DH * 2;
constexpr int NS = 5;
constexpr int NSX = 6;
constexpr int MAXG = 132;
constexpr int NROLE = 128;
constexpr int NMLP = 96;
constexpr int NFIN = 80;
constexpr int NEARLY = 12;
constexpr int NDIRECT = 4;
constexpr int YCNT = NROLE * NB - 4 * NDIRECT;
constexpr int NGO = 16;
constexpr int PSLOTS = 8;

#define WQ_DELAY 3600
#define MERGE_MARGIN 2
#define YWAIT 600
#define ZWAIT 3500

constexpr int NCONS_WARPS = 4;
constexpr int NHELP_WARPS = 8;
constexpr int NTHREADS = (NCONS_WARPS + NHELP_WARPS + 1) * 32;

constexpr int OFF_RING = 0;
constexpr int OFF_W1 = OFF_RING + NS * TILE_BYTES;
constexpr int OFF_W2 = OFF_W1 + 20480;
constexpr int OFF_WQO = OFF_W2 + 20480;
constexpr int OFF_MISC = OFF_WQO + 61440;
constexpr int OFF_HROW2 = OFF_RING + NSX * TILE_BYTES;
constexpr int OFF_RED_Q = OFF_HROW2 + 5120;
constexpr int OFF_QRAW = OFF_MISC;
constexpr int OFF_DONE = OFF_QRAW + 2048;
constexpr int OFF_HROW = OFF_DONE + 64;
constexpr int OFF_RED1 = OFF_HROW + 2560;
constexpr int OFF_SBUF = OFF_RED1 + 1024;
constexpr int OFF_STATS = OFF_SBUF + 512;
constexpr int OFF_FRED = OFF_STATS + 192;
constexpr int OFF_OBF = OFF_FRED + 384;
constexpr int OFF_META = OFF_OBF + 128;
constexpr int OFF_EPOCH = OFF_META + 32;
constexpr int OFF_BARS = OFF_EPOCH + 16;
constexpr int NBARS = 2 * NSX + 4;
constexpr int SMEM_BYTES = OFF_BARS + NBARS * 8 + 8;
static_assert(SMEM_BYTES <= 232448, "smem");
static_assert(OFF_RED_Q + 9 * 96 * 4 <= OFF_WQO, "q scratch");
static_assert(OFF_EPOCH % 16 == 0 && OFF_W2 % 1024 == 0 && OFF_WQO % 1024 == 0, "align");

constexpr float SM_SCALE = 0.07216878364870322f;
constexpr float LOG2E = 1.4426950408889634f;
constexpr float LN_EPS = 1e-5f;

struct __align__(128) Counter64 { unsigned long long v; unsigned long long pad[15]; };
struct __align__(128) Counter32 { unsigned v; unsigned pad[31]; };
__device__ Counter64 g_claim;
__device__ Counter32 g_ycnt;
__device__ Counter32 g_epoch;
__device__ __align__(128) uint4 g_qll[NBH * 32];
__device__ __align__(128) uint4 g_hdr[PSLOTS * MAXG];
__device__ __align__(128) uint4 g_done[NBH];
__device__ __align__(128) uint4 g_dat[PSLOTS * 4 * 8 * MAXG];
__device__ __align__(128) float g_hacc[2][NB * DM];
__device__ __align__(128) uint4 g_y[NDIRECT * 4 * 256];
__device__ __align__(128) uint4 g_go[NGO * 8];
__device__ __align__(128) uint4 g_z[NMLP * DM];

#define TPDECL(n) do { } while (0)
#define TP(i) do { } while (0)
#define TPOUT(slot, i) do { } while (0)
#define PROF(slot) do { } while (0)
#define PROF_REF() do { } while (0)
#define PROF_REF2() do { } while (0)

__device__ __forceinline__ uint32_t smem_u32(const void* p) { return (uint32_t)__cvta_generic_to_shared(p); }
__device__ __forceinline__ void mbar_init(uint32_t bar, uint32_t cnt) {
    asm volatile("mbarrier.init.shared::cta.b64 [%0], %1;" :: "r"(bar), "r"(cnt) : "memory");
}
__device__ __forceinline__ void mbar_expect_tx(uint32_t bar, uint32_t bytes) {
    asm volatile("mbarrier.arrive.expect_tx.shared::cta.b64 _, [%0], %1;" :: "r"(bar), "r"(bytes) : "memory");
}
__device__ __forceinline__ void mbar_arrive(uint32_t bar) {
    asm volatile("mbarrier.arrive.shared::cta.b64 _, [%0];" :: "r"(bar) : "memory");
}
__device__ __forceinline__ bool mbar_try(uint32_t bar, uint32_t parity) {
    uint32_t ok;
    asm volatile("{\n.reg .pred p;\nmbarrier.try_wait.parity.shared::cta.b64 p, [%1], %2;\nselp.u32 %0, 1, 0, p;\n}"
                 : "=r"(ok) : "r"(bar), "r"(parity) : "memory");
    return ok != 0;
}
constexpr long long SPIN_LIMIT = 4000000000LL;
__device__ __forceinline__ void spin_check(long long t0) { if (clock64() - t0 > SPIN_LIMIT) __trap(); }
__device__ __forceinline__ void busy_until(long long t) { while (clock64() < t) { } }
__device__ __forceinline__ void mbar_wait(uint32_t bar, uint32_t parity) {
    if (mbar_try(bar, parity)) return;
    const long long t0 = clock64();
    while (!mbar_try(bar, parity)) spin_check(t0);
}
__device__ __forceinline__ void tma2d_hint(uint32_t dst, const CUtensorMap* tm, int c0, int c1, uint32_t bar, uint64_t pol) {
    asm volatile("cp.async.bulk.tensor.2d.shared::cluster.global.mbarrier::complete_tx::bytes.L2::cache_hint [%0], [%1, {%3, %4}], [%2], %5;"
                 :: "r"(dst), "l"(tm), "r"(bar), "r"(c0), "r"(c1), "l"(pol) : "memory");
}
__device__ __forceinline__ void tma3d(uint32_t dst, const CUtensorMap* tm, int c0, int c1, int c2, uint32_t bar) {
    asm volatile("cp.async.bulk.tensor.3d.shared::cluster.global.mbarrier::complete_tx::bytes [%0], [%1, {%3, %4, %5}], [%2];"
                 :: "r"(dst), "l"(tm), "r"(bar), "r"(c0), "r"(c1), "r"(c2) : "memory");
}
__device__ __forceinline__ void fence_proxy_async() { asm volatile("fence.proxy.async;" ::: "memory"); }
__device__ __forceinline__ void named_bar(int id, int nthreads) {
    asm volatile("bar.sync %0, %1;" :: "r"(id), "r"(nthreads) : "memory");
}
__device__ __forceinline__ void ldsm4(uint32_t (&r)[4], uint32_t addr) {
    asm volatile("ldmatrix.sync.aligned.m8n8.x4.shared.b16 {%0,%1,%2,%3}, [%4];"
                 : "=r"(r[0]), "=r"(r[1]), "=r"(r[2]), "=r"(r[3]) : "r"(addr) : "memory");
}
__device__ __forceinline__ void ldsm4t(uint32_t (&r)[4], uint32_t addr) {
    asm volatile("ldmatrix.sync.aligned.m8n8.x4.trans.shared.b16 {%0,%1,%2,%3}, [%4];"
                 : "=r"(r[0]), "=r"(r[1]), "=r"(r[2]), "=r"(r[3]) : "r"(addr) : "memory");
}
__device__ __forceinline__ void mma16816(float (&c)[4], const uint32_t (&a)[4], uint32_t b0, uint32_t b1) {
    asm volatile("mma.sync.aligned.m16n8k16.row.col.f32.bf16.bf16.f32 {%0,%1,%2,%3}, {%4,%5,%6,%7}, {%8,%9}, {%0,%1,%2,%3};"
                 : "+f"(c[0]), "+f"(c[1]), "+f"(c[2]), "+f"(c[3])
                 : "r"(a[0]), "r"(a[1]), "r"(a[2]), "r"(a[3]), "r"(b0), "r"(b1));
}
__device__ __forceinline__ uint32_t pack_bf16(float lo, float hi) {
    uint32_t r;
    asm("cvt.rn.bf16x2.f32 %0, %1, %2;" : "=r"(r) : "f"(hi), "f"(lo));
    return r;
}
__device__ __forceinline__ float rbf(float x) { return __uint_as_float(pack_bf16(0.f, x) & 0xffff0000u); }
__device__ __forceinline__ float sqrt_fast(float x) { float y; asm("sqrt.approx.f32 %0, %1;" : "=f"(y) : "f"(x)); return y; }
__device__ __forceinline__ float rcp_fast(float x) { float y; asm("rcp.approx.f32 %0, %1;" : "=f"(y) : "f"(x)); return y; }
__device__ __forceinline__ float ex2(float x) { float y; asm("ex2.approx.ftz.f32 %0, %1;" : "=f"(y) : "f"(x)); return y; }
__device__ __forceinline__ void st_ll(uint4* p, uint32_t a, uint32_t b, uint32_t c, uint32_t d) {
    unsigned long long lo = (unsigned long long)a | ((unsigned long long)b << 32);
    unsigned long long hi = (unsigned long long)c | ((unsigned long long)d << 32);
    asm volatile("{\n.reg .b128 t;\nmov.b128 t, {%1, %2};\nst.relaxed.gpu.global.b128 [%0], t;\n}" :: "l"(p), "l"(lo), "l"(hi) : "memory");
}
__device__ __forceinline__ uint4 ld_ll(const uint4* p) {
    unsigned long long lo, hi;
    asm volatile("{\n.reg .b128 t;\nld.relaxed.gpu.global.b128 t, [%2];\nmov.b128 {%0, %1}, t;\n}" : "=l"(lo), "=l"(hi) : "l"(p) : "memory");
    uint4 r; r.x = (uint32_t)lo; r.y = (uint32_t)(lo >> 32); r.z = (uint32_t)hi; r.w = (uint32_t)(hi >> 32);
    return r;
}
__device__ __forceinline__ unsigned ld_relaxed_u32(const unsigned* p) {
    unsigned v; asm volatile("ld.relaxed.gpu.global.u32 %0, [%1];" : "=r"(v) : "l"(p) : "memory"); return v;
}
__device__ __forceinline__ unsigned long long ld_relaxed_u64(const unsigned long long* p) {
    unsigned long long v; asm volatile("ld.relaxed.gpu.global.u64 %0, [%1];" : "=l"(v) : "l"(p) : "memory"); return v;
}
__device__ __forceinline__ float ld_relaxed_f32(const float* p) {
    float v; asm volatile("ld.relaxed.gpu.global.f32 %0, [%1];" : "=f"(v) : "l"(p) : "memory"); return v;
}
__device__ __forceinline__ void fence_gpu() { asm volatile("fence.acq_rel.gpu;" ::: "memory"); }
__device__ __forceinline__ void red_add_u32(unsigned* p, unsigned v) {
    asm volatile("red.relaxed.gpu.global.add.u32 [%0], %1;" :: "l"(p), "r"(v) : "memory");
}
__device__ __forceinline__ void red_add_f32(float* p, float v) {
    asm volatile("red.relaxed.gpu.global.add.f32 [%0], %1;" :: "l"(p), "f"(v) : "memory");
}
__device__ __forceinline__ void wait_counter(const unsigned* p, unsigned target, unsigned sleep_ns) {
    const long long t0 = clock64();
    while (true) {
        unsigned v;
        asm volatile("ld.acquire.gpu.global.u32 %0, [%1];" : "=r"(v) : "l"(p) : "memory");
        if ((int)(v - target) >= 0) break;
        __nanosleep(sleep_ns); spin_check(t0);
    }
}
__device__ __forceinline__ void cp_async16(uint32_t dst, const void* src) {
    asm volatile("cp.async.cg.shared.global [%0], [%1], 16;" :: "r"(dst), "l"(src) : "memory");
}
__device__ __forceinline__ void cp_async_commit() { asm volatile("cp.async.commit_group;" ::: "memory"); }
__device__ __forceinline__ void cp_async_wait_all() { asm volatile("cp.async.wait_all;" ::: "memory"); }
__device__ __forceinline__ uint4 lds128(uint32_t addr) {
    uint4 r;
    asm volatile("ld.shared.v4.u32 {%0,%1,%2,%3}, [%4];" : "=r"(r.x), "=r"(r.y), "=r"(r.z), "=r"(r.w) : "r"(addr) : "memory");
    return r;
}
__device__ __forceinline__ void sts128(uint32_t addr, uint4 v) {
    asm volatile("st.shared.v4.u32 [%0], {%1,%2,%3,%4};" :: "r"(addr), "r"(v.x), "r"(v.y), "r"(v.z), "r"(v.w) : "memory");
}
__device__ __forceinline__ float warp_max(float v) {
    int i = __float_as_int(v);
    i ^= (i >> 31) & 0x7fffffff;
    i = __reduce_max_sync(0xffffffffu, i);
    i ^= (i >> 31) & 0x7fffffff;
    return __int_as_float(i);
}

__device__ __forceinline__ void ln_row(const float (&v)[3], float c, __nv_bfloat16* hn, float2* stats, int hw, int lane) {
    const int g = lane >> 2, j = lane & 3;
    const bool full = j < 3;
    const float d0 = v[0] - c, d1 = full ? v[1] - c : 0.f, d2 = full ? v[2] - c : 0.f;
    float s1 = (d0 + d1) + d2, s2 = fmaf(d0, d0, fmaf(d1, d1, d2 * d2));
#pragma unroll
    for (int o = 16; o >= 1; o >>= 1) { s1 += __shfl_xor_sync(0xffffffffu, s1, o); s2 += __shfl_xor_sync(0xffffffffu, s2, o); }
    if (lane == 0) stats[hw] = make_float2(s1, s2);
    named_bar(2, NHELP_WARPS * 32);
    const float4* sp = reinterpret_cast<const float4*>(stats);
    const float4 a = sp[0], b = sp[1], cc = sp[2], d = sp[3];
    const float S1 = (((a.x + a.z) + (b.x + b.z)) + ((cc.x + cc.z) + (d.x + d.z))) * (1.0f / DM);
    const float S2 = (((a.y + a.w) + (b.y + b.w)) + ((cc.y + cc.w) + (d.y + d.w))) * (1.0f / DM);
    const float mb = rbf(c + S1);
    const float rinv = rcp_fast(rbf(sqrt_fast(rbf(rbf(fmaxf(fmaf(-S1, S1, S2), 0.f)) + LN_EPS))));
    __nv_bfloat16* hp = hn + 80 * hw + 24 * j + g;
    hp[0] = __float2bfloat16(rbf(v[0] - mb) * rinv);
    if (full) { hp[8] = __float2bfloat16(rbf(v[1] - mb) * rinv); hp[16] = __float2bfloat16(rbf(v[2] - mb) * rinv); }
    __syncwarp();
}
__device__ __forceinline__ float row_mean(const float (&v)[3], float* st8, int hw, int lane) {
    const bool full = (lane & 3) < 3;
    float s1 = v[0] + (full ? v[1] + v[2] : 0.f);
#pragma unroll
    for (int o = 16; o >= 1; o >>= 1) s1 += __shfl_xor_sync(0xffffffffu, s1, o);
    if (lane == 0) st8[hw] = s1;
    named_bar(2, NHELP_WARPS * 32);
    const float4 a = *reinterpret_cast<const float4*>(st8), b = *reinterpret_cast<const float4*>(st8 + 4);
    return (((a.x + a.y) + (a.z + a.w)) + ((b.x + b.y) + (b.z + b.w))) * (1.0f / DM);
}

__device__ __forceinline__ void ln_rows2(const float (&v)[2][3], float* hrow2, float4* stats, int hw, int lane, uint32_t (&fr)[5][2]) {
    const int g = lane >> 2, j = lane & 3;
    const bool full = j < 3;
    float* hp = hrow2 + 80 * hw + 24 * j + g;
    hp[0] = v[0][0]; hp[DM] = v[1][0];
    if (full) { hp[8] = v[0][1]; hp[16] = v[0][2]; hp[DM + 8] = v[1][1]; hp[DM + 16] = v[1][2]; }
    float c[2], s1[2], s2[2];
#pragma unroll
    for (int r = 0; r < 2; r++) {
        c[r] = __shfl_sync(0xffffffffu, v[r][0], 0);
        const float d0 = v[r][0] - c[r], d1 = full ? v[r][1] - c[r] : 0.f, d2 = full ? v[r][2] - c[r] : 0.f;
        s1[r] = d0 + d1 + d2; s2[r] = d0 * d0 + d1 * d1 + d2 * d2;
    }
#pragma unroll
    for (int o = 16; o >= 1; o >>= 1) {
#pragma unroll
        for (int r = 0; r < 2; r++) { s1[r] += __shfl_xor_sync(0xffffffffu, s1[r], o); s2[r] += __shfl_xor_sync(0xffffffffu, s2[r], o); }
    }
    if (lane == 0) stats[hw] = make_float4(c[0] + s1[0] * (1.0f / 80.0f), s2[0] - s1[0] * s1[0] * (1.0f / 80.0f),
                                           c[1] + s1[1] * (1.0f / 80.0f), s2[1] - s1[1] * s1[1] * (1.0f / 80.0f));
    named_bar(2, NHELP_WARPS * 32);
    const int row = g & 1;
    const float2* sp = reinterpret_cast<const float2*>(stats) + row;
    float mw[8], m2 = 0.f, mean = 0.f;
#pragma unroll
    for (int k = 0; k < 8; k++) { const float2 t = sp[2 * k]; mw[k] = t.x; mean += t.x; m2 += t.y; }
    mean *= 0.125f;
    float dev = 0.f;
#pragma unroll
    for (int k = 0; k < 8; k++) dev += (mw[k] - mean) * (mw[k] - mean);
    const float mb = rbf(mean);
    const float rinv = rcp_fast(rbf(sqrt_fast(rbf(rbf(fmaxf(m2 + 80.0f * dev, 0.f) * (1.0f / DM)) + LN_EPS))));
    const float* fp = hrow2 + row * DM + 80 * hw + 2 * j;
#pragma unroll
    for (int i = 0; i < 5; i++) {
        const float2 p = *reinterpret_cast<const float2*>(fp + 16 * i);
        const float2 q = *reinterpret_cast<const float2*>(fp + 16 * i + 8);
        fr[i][0] = (g < 2) ? pack_bf16(rbf(p.x - mb) * rinv, rbf(p.y - mb) * rinv) : 0u;
        fr[i][1] = (g < 2) ? pack_bf16(rbf(q.x - mb) * rinv, rbf(q.y - mb) * rinv) : 0u;
    }
}

__global__ void __launch_bounds__(NTHREADS, 1)
fused_decode_kernel(const __grid_constant__ CUtensorMap tmK, const __grid_constant__ CUtensorMap tmV,
                    const __grid_constant__ CUtensorMap tmWo, const __grid_constant__ CUtensorMap tmW2,
                    const char* __restrict__ kc, const char* __restrict__ vc,
                    const __nv_bfloat16* __restrict__ x, const __nv_bfloat16* __restrict__ wq,
                    const __nv_bfloat16* __restrict__ w1, const __nv_bfloat16* __restrict__ w2, __nv_bfloat16* __restrict__ out)
{
    extern __shared__ __align__(1024) unsigned char smem[];
    const uint32_t sbase = smem_u32(smem);
    const int tid = threadIdx.x, warp = tid >> 5, lane = tid & 31;
    const int cta = blockIdx.x, G = gridDim.x;

    const uint32_t bar_full = sbase + OFF_BARS;
    const uint32_t bar_empty = bar_full + NSX * 8;
    const uint32_t bar_wo = bar_empty + NSX * 8;
    const uint32_t bar_w1 = bar_wo + 8;
    const uint32_t bar_w2 = bar_w1 + 8;
    const uint32_t bar_cdone = bar_w2 + 8;
    volatile int* meta = reinterpret_cast<volatile int*>(smem + OFF_META);

    uint64_t pol = 0;
    const long long tstart = clock64();
    if (tid == NTHREADS - 32) {
        asm volatile("cp.async.bulk.prefetch.L2.global [%0], %1;" :: "l"(kc + (size_t)cta * TILE_BYTES), "r"(TILE_BYTES) : "memory");
        asm volatile("cp.async.bulk.prefetch.L2.global [%0], %1;" :: "l"(vc + (size_t)cta * TILE_BYTES), "r"(TILE_BYTES) : "memory");
    }
    const int ht = tid - NCONS_WARPS * 32;
    auto load_wq = [&]() {
        const __nv_bfloat16* src = wq + cta * 48;
#pragma unroll
        for (int i = 0; i < 15; i++) {
            const int idx = ht + 256 * i, row = idx / 6, u = idx - 6 * row;
            cp_async16(sbase + OFF_WQO + idx * 16, src + (size_t)row * (NH * DH) + u * 8);
        }
        cp_async_commit();
    };
    if (warp >= NCONS_WARPS && warp < NCONS_WARPS + NHELP_WARPS && cta < NROLE) {
        if (ht < 160) cp_async16(sbase + OFF_HROW + ht * 16, x + ht * 8);
        if (ht == 160) cp_async16(sbase + OFF_EPOCH, &g_epoch);
        cp_async_commit();
        if (cta < NEARLY) load_wq();
    }
    if (warp == NCONS_WARPS + NHELP_WARPS && lane == 0) {
        PROF(0);
        for (int i = 0; i < NSX; i++) { mbar_init(bar_full + 8 * i, 1); mbar_init(bar_empty + 8 * i, NCONS_WARPS); }
        mbar_init(bar_wo, 1); mbar_init(bar_w1, 32); mbar_init(bar_w2, 1); mbar_init(bar_cdone, NCONS_WARPS);
        asm volatile("fence.mbarrier_init.release.cluster;" ::: "memory");
        asm volatile("fence.proxy.async.shared::cta;" ::: "memory");
        asm volatile("createpolicy.fractional.L2::evict_first.b64 %0, 1.0;" : "=l"(pol));
        meta[0] = cta;
        mbar_expect_tx(bar_full, TILE_BYTES);
        tma2d_hint(sbase + OFF_RING, &tmK, 0, cta * 192, bar_full, pol);
        mbar_expect_tx(bar_full + 8, TILE_BYTES);
        tma2d_hint(sbase + OFF_RING + TILE_BYTES, &tmV, 0, cta * 192, bar_full + 8, pol);
    }
    __syncthreads();

    if (warp == NCONS_WARPS + NHELP_WARPS) {
        asm volatile("setmaxnreg.dec.sync.aligned.u32 40;");
        if (lane == 0) {
            unsigned long long old = atomicAdd(&g_claim.v, 1ULL);
            PROF_REF();
            int slot = 2, lim = NSX; uint32_t ph = 1;
            int wslot = 0, wlim = NSX; uint32_t wph = 0;
            while (true) {
                const int unit = (int)(old & (NUNITS - 1)) + G;
                if (unit >= NUNITS) break;
                mbar_wait(bar_full + 8 * wslot, wph); if (++wslot == wlim) { wslot = 0; wph ^= 1; wlim = NS; }
                mbar_wait(bar_empty + 8 * slot, ph);
                meta[slot] = unit;
                mbar_expect_tx(bar_full + 8 * slot, TILE_BYTES);
                tma2d_hint(sbase + OFF_RING + slot * TILE_BYTES, &tmK, 0, unit * 192, bar_full + 8 * slot, pol);
                if (++slot == lim) { slot = 0; ph ^= 1; lim = NS; }
                mbar_wait(bar_full + 8 * wslot, wph); if (++wslot == wlim) { wslot = 0; wph ^= 1; wlim = NS; }
                mbar_wait(bar_empty + 8 * slot, ph);
                mbar_expect_tx(bar_full + 8 * slot, TILE_BYTES);
                tma2d_hint(sbase + OFF_RING + slot * TILE_BYTES, &tmV, 0, unit * 192, bar_full + 8 * slot, pol);
                if (++slot == lim) { slot = 0; ph ^= 1; lim = NS; }
                old = atomicAdd(&g_claim.v, 1ULL);
            }
            PROF(2);
            PROF_REF2();
            mbar_wait(bar_empty + 8 * slot, ph);
            meta[slot] = -1;
            mbar_arrive(bar_full + 8 * slot);
        }
        __syncwarp();
        if (cta < NMLP) {
            const __nv_bfloat16* src = w1 + cta * 16;
#pragma unroll 4
            for (int i = 0; i < 40; i++) {
                const int idx = lane + 32 * i;
                cp_async16(sbase + OFF_W1 + idx * 16, src + (size_t)(idx >> 1) * DFF + (idx & 1) * 8);
            }
            asm volatile("cp.async.mbarrier.arrive.noinc.shared::cta.b64 [%0];" :: "r"(bar_w1) : "memory");
            if (lane == 0) {
                fence_proxy_async();
                mbar_expect_tx(bar_w2, 20480);
                tma3d(sbase + OFF_W2, &tmW2, 0, 0, cta * 16, bar_w2);
            }
            cp_async_wait_all();
        }
    } else if (warp < NCONS_WARPS) {
        asm volatile("setmaxnreg.dec.sync.aligned.u32 96;");
        const int w = warp, g = lane >> 2, j = lane & 3;
        uint4* const dat_base = g_dat + ((size_t)w * 8 + g) * MAXG + cta;
        uint4* const hdr_base = g_hdr + cta;
        const uint32_t epoch = ld_relaxed_u32(&g_epoch.v);
        const uint32_t flag = epoch + 1u;
        uint32_t koff[3];
        {
            const int key = 16 * w + (lane & 7) + 8 * ((lane >> 3) & 1), hi = lane >> 4;
#pragma unroll
            for (int c = 0; c < 3; c++) { const int r = key * 3 + c; koff[c] = r * 128 + (((r & 7) ^ hi) << 4); }
        }
        uint32_t voff[3];
        {
            const int key = (lane & 7) + 8 * (lane >> 4), hi = (lane >> 3) & 1;
#pragma unroll
            for (int mt = 0; mt < 3; mt++) {
                const int U = 6 * w + 2 * mt + hi, c = U >> 3, u = U & 7, r = key * 3 + c;
                voff[mt] = r * 128 + ((u ^ (r & 7)) << 4);
            }
        }
        const bool act = (g >> 1) == j;
        const uint32_t sel0 = act ? ((g & 1) ? 0x1044u : 0x4410u) : 0x4444u;
        const uint32_t sel1 = act ? ((g & 1) ? 0x3244u : 0x4432u) : 0x4444u;
        float* sbuf = reinterpret_cast<float*>(smem + OFF_SBUF);
        const uint32_t qraw = sbase + OFF_QRAW + w * 512;
        const uint32_t dnraw = sbase + OFF_DONE + w * 16;

        uint32_t qf[24];
        float o[3][4];
        float m_run = -INFINITY, l_run = 0.f;
        int cur_bh = -1, pre_bh = -1, done_bh = -1, par = 0;
        int slot = 0, lim = NSX; uint32_t ph = 0;

        auto advance_to = [&](int nb) {
#pragma unroll 1
            while (cur_bh < nb) {
                if (cur_bh >= 0) {
                    if (cur_bh >= PSLOTS) {
                        uint4 dn = lds128(dnraw);
                        if (done_bh != cur_bh - PSLOTS || dn.x != flag || dn.y != flag || dn.z != flag || dn.w != flag) {
                            const long long t0 = clock64();
                            do { dn = ld_ll(g_done + cur_bh - PSLOTS); spin_check(t0); } while (dn.x != flag || dn.y != flag || dn.z != flag || dn.w != flag);
                        }
                    }
                    const uint32_t tag = flag * 8u + (uint32_t)(cur_bh >> 3);
                    float lo[3], hi[3];
#pragma unroll
                    for (int mt = 0; mt < 3; mt++) {
                        lo[mt] = o[mt][0] + o[mt][1]; hi[mt] = o[mt][2] + o[mt][3];
                        lo[mt] += __shfl_xor_sync(0xffffffffu, lo[mt], 1); hi[mt] += __shfl_xor_sync(0xffffffffu, hi[mt], 1);
                        lo[mt] += __shfl_xor_sync(0xffffffffu, lo[mt], 2); hi[mt] += __shfl_xor_sync(0xffffffffu, hi[mt], 2);
                    }
                    if (j == 0)
                        st_ll(dat_base + (cur_bh & (PSLOTS - 1)) * (4 * 8 * MAXG), pack_bf16(lo[0], hi[0]), pack_bf16(lo[1], hi[1]), pack_bf16(lo[2], hi[2]), tag);
                    if (w == 0) {
                        float l = l_run;
                        l += __shfl_xor_sync(0xffffffffu, l, 4);
                        l += __shfl_xor_sync(0xffffffffu, l, 8);
                        l += __shfl_xor_sync(0xffffffffu, l, 16);
                        if (lane == 1) st_ll(hdr_base + (cur_bh & (PSLOTS - 1)) * MAXG, __float_as_uint(m_run), __float_as_uint(l), 0u, tag);
                    }
                }
                m_run = -INFINITY; l_run = 0.f;
#pragma unroll
                for (int mt = 0; mt < 3; mt++) { o[mt][0] = o[mt][1] = o[mt][2] = o[mt][3] = 0.f; }
                cur_bh++;
            }
        };

        {
            if (w == 0) {
                const long long t0 = clock64();
                const uint4* qp = g_qll + lane;
                uint4 r0 = ld_ll(qp);
                while (!__all_sync(0xffffffffu, r0.w == flag)) { __nanosleep(200); r0 = ld_ll(qp); spin_check(t0); }
#pragma unroll
                for (int k = 0; k < NCONS_WARPS; k++) sts128(sbase + OFF_QRAW + k * 512 + lane * 16, r0);
            }
            named_bar(1, NCONS_WARPS * 32);
            pre_bh = 0;
            if (w == 0 && lane == 0) PROF(1);
        }

        while (true) {
            mbar_wait(bar_full + 8 * slot, ph);
            const int unit = meta[slot];
            if (unit < 0) break;
            const int bh = unit >> 8;
            if (bh != cur_bh) {
                cp_async_wait_all();
                __syncwarp();
                advance_to(bh);
                bool have = false;
                if (pre_bh == bh) {
                    bool ok = true;
#pragma unroll
                    for (int t = 0; t < 8; t++) {
                        const uint4 r = lds128(qraw + (j * 8 + t) * 16);
                        qf[3 * t] = r.x; qf[3 * t + 1] = r.y; qf[3 * t + 2] = r.z;
                        ok = ok && (r.w == flag);
                    }
                    have = __all_sync(0xffffffffu, ok);
                }
                if (!have) {
                    const long long t0 = clock64();
                    const uint4* qp = g_qll + bh * 32 + lane;
                    uint4 r0 = ld_ll(qp);
                    while (!__all_sync(0xffffffffu, r0.w == flag)) { __nanosleep(200); r0 = ld_ll(qp); spin_check(t0); }
                    sts128(qraw + lane * 16, r0);
                    __syncwarp();
#pragma unroll
                    for (int t = 0; t < 8; t++) {
                        const uint4 r = lds128(qraw + (j * 8 + t) * 16);
                        qf[3 * t] = r.x; qf[3 * t + 1] = r.y; qf[3 * t + 2] = r.z;
                    }
                }
                __syncwarp();
                pre_bh = bh + 1;
                if (pre_bh < NBH) cp_async16(qraw + lane * 16, g_qll + pre_bh * 32 + lane);
                done_bh = bh - PSLOTS;
                if (done_bh >= 0 && lane == 0) cp_async16(dnraw, g_done + done_bh);
            }
            float s0[4] = {0.f, 0.f, 0.f, 0.f}, s1[4] = {0.f, 0.f, 0.f, 0.f}, s2[4] = {0.f, 0.f, 0.f, 0.f};
            {
                const uint32_t kb = sbase + OFF_RING + slot * TILE_BYTES;
#pragma unroll
                for (int i = 0; i < 4; i++) {
                    uint32_t a[4], b[4], c[4];
                    ldsm4(a, kb + (koff[0] ^ (i * 32)));
                    ldsm4(b, kb + (koff[1] ^ (i * 32)));
                    ldsm4(c, kb + (koff[2] ^ (i * 32)));
                    mma16816(s0, a, qf[2 * i], qf[2 * i + 1]);
                    mma16816(s1, b, qf[8 + 2 * i], qf[8 + 2 * i + 1]);
                    mma16816(s2, c, qf[16 + 2 * i], qf[16 + 2 * i + 1]);
                }
            }
            const float slo = rbf(rbf(s0[0] + s1[0] + s2[0]) * SM_SCALE), shi = rbf(rbf(s0[2] + s1[2] + s2[2]) * SM_SCALE);
            __syncwarp();
            if (lane == 0) mbar_arrive(bar_empty + 8 * slot);
            if (++slot == lim) { slot = 0; ph ^= 1; lim = NS; }
            float* sb = sbuf + par * 64;
            if (j == 0) { sb[16 * w + g] = slo; sb[16 * w + 8 + g] = shi; }
            par ^= 1;
            named_bar(1, NCONS_WARPS * 32);
            float sv[8];
#pragma unroll
            for (int kk = 0; kk < 4; kk++) { sv[2 * kk] = sb[16 * kk + g]; sv[2 * kk + 1] = sb[16 * kk + 8 + g]; }
            float mx = fmaxf(fmaxf(fmaxf(sv[0], sv[1]), fmaxf(sv[2], sv[3])), fmaxf(fmaxf(sv[4], sv[5]), fmaxf(sv[6], sv[7])));
            mx = warp_max(mx);
            const float m_new = fmaxf(m_run, mx);
            const float mc = m_new * LOG2E;
            const float alpha = ex2(m_run * LOG2E - mc);
            m_run = m_new;
            uint32_t pb[4][2];
            float psum = 0.f;
#pragma unroll
            for (int kk = 0; kk < 4; kk++) {
                const float p0 = ex2(fmaf(sv[2 * kk], LOG2E, -mc));
                const float p1 = ex2(fmaf(sv[2 * kk + 1], LOG2E, -mc));
                psum += p0 + p1;
                const uint32_t pk = pack_bf16(p0, p1);
                pb[kk][0] = __byte_perm(pk, 0u, sel0);
                pb[kk][1] = __byte_perm(pk, 0u, sel1);
            }
            l_run = l_run * alpha + psum;
#pragma unroll
            for (int mt = 0; mt < 3; mt++) { o[mt][0] *= alpha; o[mt][1] *= alpha; o[mt][2] *= alpha; o[mt][3] *= alpha; }
            mbar_wait(bar_full + 8 * slot, ph);
            {
                const uint32_t vb = sbase + OFF_RING + slot * TILE_BYTES;
#pragma unroll
                for (int k2 = 0; k2 < 4; k2 += 2) {
                    uint32_t a[2][3][4];
#pragma unroll
                    for (int kk = 0; kk < 2; kk++)
#pragma unroll
                        for (int mt = 0; mt < 3; mt++) ldsm4t(a[kk][mt], vb + voff[mt] + (k2 + kk) * 6144);
#pragma unroll
                    for (int kk = 0; kk < 2; kk++)
#pragma unroll
                        for (int mt = 0; mt < 3; mt++) mma16816(o[mt], a[kk][mt], pb[k2 + kk][0], pb[k2 + kk][1]);
                }
            }
            __syncwarp();
            if (lane == 0) mbar_arrive(bar_empty + 8 * slot);
            if (++slot == lim) { slot = 0; ph ^= 1; lim = NS; }
        }
        cp_async_wait_all();
        __syncwarp();
        advance_to(NBH);
        if (lane == 0) mbar_arrive(bar_cdone);
        if (w == 0 && lane == 0) PROF(3);
        __syncwarp();
        if (cta < NFIN) {
            TPDECL(4);
            const int nn = lane & 7, sub = lane >> 3;
            const int n = 8 * cta + nn;
            const long long t0 = clock64();
            float* fred = reinterpret_cast<float*>(smem + OFF_FRED);
            const int hw2 = n / 80, r = n - 80 * hw2, idx = r >> 3, jj = idx / 3, tt = idx - 3 * jj;
            const int yoff = sub * 256 + hw2 * 32 + nn * 4 + jj;
            const uint4* zp = g_z + (size_t)(24 * w + sub) * DM + n;
            float xb = 0.f, abase = 0.f, yv = 0.f;
            if (lane < 4) { while (ld_ll(g_go + ((cta + 4 * w) & (NGO - 1)) * 8 + lane).w != flag) spin_check(t0); }
            __syncwarp();
            TP(0);
            const long long t1 = clock64();
#pragma unroll 1
            for (int pass = 0; pass < 2; pass++) {
                if (pass) {
                    if (w == 0) {
                        if (lane == 0) wait_counter(&g_ycnt.v, flag * YCNT, 100);
                        __syncwarp();
                        if (lane < 16) { xb = __bfloat162float(x[sub * DM + n]); abase = ld_relaxed_f32(g_hacc[epoch & 1] + sub * DM + n); }
                    }
                    {
                        if (w == NDIRECT - 1) busy_until(t1 + YWAIT + 300);
                        const uint4* yp = g_y + w * 1024 + yoff;
                        uint4 d = ld_ll(yp);
                        while (d.w != flag) { d = ld_ll(yp); spin_check(t0); }
                        yv = __uint_as_float(tt == 0 ? d.x : (tt == 1 ? d.y : d.z));
                    }
                    busy_until(t1 + ZWAIT);
                }
                uint4 d[6];
#pragma unroll
                for (int s = 0; s < 6; s++) d[s] = make_uint4(0u, 0u, 0u, pass ? flag - 1u : flag);
                while (true) {
                    bool ok = true;
#pragma unroll
                    for (int s = 0; s < 6; s++) { if (d[s].w != flag) d[s] = ld_ll(zp + (size_t)4 * s * DM); }
#pragma unroll
                    for (int s = 0; s < 6; s++) ok = ok && d[s].w == flag;
                    if (ok) break;
                    spin_check(t0);
                }
                float z0 = 0.f, z1 = 0.f, ya = yv;
#pragma unroll
                for (int s = 0; s < 6; s++) { z0 += __uint_as_float(d[s].x); z1 += __uint_as_float(d[s].y); }
                __syncwarp();
                TP(1);
                z0 += __shfl_xor_sync(0xffffffffu, z0, 8); z1 += __shfl_xor_sync(0xffffffffu, z1, 8); ya += __shfl_xor_sync(0xffffffffu, ya, 8);
                z0 += __shfl_xor_sync(0xffffffffu, z0, 16); z1 += __shfl_xor_sync(0xffffffffu, z1, 16); ya += __shfl_xor_sync(0xffffffffu, ya, 16);
                if (lane < 8) { fred[w * 24 + nn] = z0; fred[w * 24 + 8 + nn] = z1; fred[w * 24 + 16 + nn] = ya; }
                named_bar(1, NCONS_WARPS * 32);
                if (w == 0 && lane < 16) {
                    const float mlp = (fred[lane] + fred[24 + lane]) + (fred[48 + lane] + fred[72 + lane]);
                    const float yd = (fred[16 + nn] + fred[40 + nn]) + (fred[64 + nn] + fred[88 + nn]);
                    const float h = rbf(xb + rbf(abase + (sub ? yd : 0.f)));
                    if (pass) out[sub * DM + n] = __float2bfloat16(h + rbf(mlp));
                }
                if (!pass) named_bar(1, NCONS_WARPS * 32);
            }
            TP(2);
            if (cta == 0 && w == 0 && lane == 0) g_epoch.v = epoch + 1u;
            if (w == 0 && lane == 0) { TPOUT(13, 0); TPOUT(14, 1); TPOUT(7, 2); }
        }
    } else {
        asm volatile("setmaxnreg.inc.sync.aligned.u32 144;");
        if (cta >= NROLE) return;
        const int hw = warp - NCONS_WARPS;
        const int g = lane >> 2, j = lane & 3;
        const int head = cta >> 2, qd = cta & 3;
        int own[3];
#pragma unroll
        for (int t = 0; t < 3; t++) own[t] = 80 * hw + 8 * ((j < 3) ? 3 * j + t : 9) + g;
        if (ht < 16) st_ll(g_qll + ((ht >> 3) * NH + head) * 32 + ((ht >> 1) & 3) * 8 + 2 * qd + (ht & 1), 0u, 0u, 0u, 0u);
        float xv[2][3];
        {
            if (cta < NEARLY) asm volatile("cp.async.wait_group 1;" ::: "memory"); else asm volatile("cp.async.wait_group 0;" ::: "memory");
            named_bar(2, NHELP_WARPS * 32);
            const __nv_bfloat16* xs = reinterpret_cast<const __nv_bfloat16*>(smem + OFF_HROW);
#pragma unroll
            for (int t = 0; t < 3; t++) { xv[0][t] = __bfloat162float(xs[own[t]]); xv[1][t] = __bfloat162float(xs[DM + own[t]]); }
        }
        const uint32_t epoch = *reinterpret_cast<const uint32_t*>(smem + OFF_EPOCH);
        const uint32_t flag = epoch + 1u;
        float* hacc = g_hacc[epoch & 1];
        float2* stats = reinterpret_cast<float2*>(smem + OFF_STATS);
        const int krow = (lane & 7) + 8 * (lane >> 4), mhi = (lane >> 3) & 1;
        auto wait_claims = [&](int target) {
            while (true) {
                const int rem = target - (int)(long long)(ld_relaxed_u64(&g_claim.v) - ((unsigned long long)epoch << 14));
                if (rem <= 0) break;
                const unsigned ns = rem > 2000 ? 8000u : (unsigned)rem * 4u;
                __nanosleep(ns < 64u ? 64u : ns);
                spin_check(tstart);
            }
        };
        TPDECL(12);

        {
            uint32_t bf[5][2];
            ln_rows2(xv, reinterpret_cast<float*>(smem + OFF_HROW2), reinterpret_cast<float4*>(smem + OFF_STATS), hw, lane, bf);
            if (ht == 0) PROF(8);
            if (cta >= NEARLY) { busy_until(tstart + WQ_DELAY); load_wq(); }
            cp_async_wait_all();
            named_bar(2, NHELP_WARPS * 32);
            if (ht == 0) PROF(9);
            float* red = reinterpret_cast<float*>(smem + OFF_RED_Q);
            float acc[3][4];
#pragma unroll
            for (int mt = 0; mt < 3; mt++) { acc[mt][0] = acc[mt][1] = acc[mt][2] = acc[mt][3] = 0.f; }
#pragma unroll
            for (int i = 0; i < 5; i++) {
                const uint32_t rowaddr = sbase + OFF_WQO + (16 * (5 * hw + i) + krow) * 96 + mhi * 16;
#pragma unroll
                for (int mt = 0; mt < 3; mt++) {
                    uint32_t a[4];
                    ldsm4t(a, rowaddr + mt * 32);
                    mma16816(acc[mt], a, bf[i][0], bf[i][1]);
                }
            }
            if (j == 0) {
#pragma unroll
                for (int mt = 0; mt < 3; mt++) {
                    red[hw * 96 + 16 * mt + g] = acc[mt][0];
                    red[hw * 96 + 48 + 16 * mt + g] = acc[mt][1];
                    red[hw * 96 + 16 * mt + 8 + g] = acc[mt][2];
                    red[hw * 96 + 48 + 16 * mt + 8 + g] = acc[mt][3];
                }
            }
            named_bar(2, NHELP_WARPS * 32);
            if (ht < 96) {
                float s = 0.f;
#pragma unroll
                for (int k = 0; k < 8; k++) s += red[k * 96 + ht];
                red[8 * 96 + ht] = s;
            }
            named_bar(2, NHELP_WARPS * 32);
            if (ht < 16) {
                const int b = ht >> 3, jj = (ht >> 1) & 3, e2 = ht & 1;
                uint32_t fw[3];
#pragma unroll
                for (int r = 0; r < 3; r++) {
                    const int rl = 3 * e2 + r;
                    const int col = 16 * (rl >> 1) + 8 * (rl & 1) + 2 * jj;
                    fw[r] = pack_bf16(red[8 * 96 + b * 48 + col], red[8 * 96 + b * 48 + col + 1]);
                }
                st_ll(g_qll + (b * NH + head) * 32 + jj * 8 + 2 * qd + e2, fw[0], fw[1], fw[2], flag);
            }
            named_bar(2, NHELP_WARPS * 32);
            if (ht == 0) {
                PROF(10);
                fence_proxy_async();
                mbar_expect_tx(bar_wo, 61440);
                tma3d(sbase + OFF_WQO, &tmWo, 0, 0, cta * 48, bar_wo);
            }
            if (head >= NH - NDIRECT) st_ll(g_y + ((head - (NH - NDIRECT)) * 4 + qd) * 256 + ht, 0u, 0u, 0u, 0u);
            if (head == NH - 1 && ht < NGO) st_ll(g_go + ht * 8 + qd, 0u, 0u, 0u, 0u);
            if (cta < NMLP) {
#pragma unroll
                for (int i = 0; i < 3; i++) if (ht + 256 * i < DM) st_ll(g_z + (size_t)cta * DM + ht + 256 * i, 0u, 0u, 0u, 0u);
            }
            if (cta == 0) {
#pragma unroll
                for (int i = 0; i < 5; i++) g_hacc[(epoch + 1) & 1][ht + 256 * i] = 0.f;
            }
        }

        __nv_bfloat16* obf = reinterpret_cast<__nv_bfloat16*>(smem + OFF_OBF);
        uint32_t wof[3][5][4];
        mbar_wait(bar_wo, 0);
#pragma unroll
        for (int i = 0; i < 5; i++) {
            const int mt = 5 * hw + i;
#pragma unroll
            for (int ks = 0; ks < 3; ks++) {
                const int line = (16 * ks + krow) * 10 + (mt >> 2);
                ldsm4t(wof[ks][i], sbase + OFF_WQO + line * 128 + (((2 * (mt & 3) + mhi) ^ (line & 7)) << 4));
            }
        }
#pragma unroll 1
        for (int b = 0; b < NB; b++) {
            const int bh = b * NH + head;
            const bool last = (bh == NBH - 1), direct = (bh >= NBH - NDIRECT);
            uint4 hd[5], dt[5];
            const uint32_t tag = flag * 8u + (uint32_t)(bh >> 3);
#pragma unroll 1
            for (int pass = last ? 0 : 1; pass < 2; pass++) {
                if (pass) {
                    if (last) mbar_wait(bar_cdone, 0);
                    else {
                        if (ht == 0) wait_claims(min((bh + 1) * TPB + (direct ? 1 : MERGE_MARGIN) * G, NUNITS - G));
                        named_bar(2, NHELP_WARPS * 32);
                    }
                } else {
                    if (ht == 0) wait_claims(NUNITS - G - 400);
                    named_bar(2, NHELP_WARPS * 32);
                }
                const uint32_t pend = pass ? tag - 1u : tag;
#pragma unroll
                for (int s = 0; s < 5; s++) {
                    const uint32_t st = (lane + 32 * s < G) ? pend : tag;
                    hd[s] = make_uint4(0xff800000u, 0u, 0u, st); dt[s] = make_uint4(0u, 0u, 0u, st);
                }
                {
                    const uint4* hp = g_hdr + (bh & (PSLOTS - 1)) * MAXG + lane;
                    const uint4* dp = g_dat + (((bh & (PSLOTS - 1)) * 4 + qd) * 8 + hw) * MAXG + lane;
                    while (true) {
#pragma unroll
                        for (int s = 0; s < 5; s++) {
                            if (dt[s].w != tag) dt[s] = ld_ll(dp + 32 * s);
                            if (hd[s].w != tag) hd[s] = ld_ll(hp + 32 * s);
                        }
                        bool ok = true;
#pragma unroll
                        for (int s = 0; s < 5; s++) ok = ok && dt[s].w == tag && hd[s].w == tag;
                        if (__all_sync(0xffffffffu, ok)) break;
                        if (!last) __nanosleep(direct ? 250 : 500);
                        spin_check(tstart);
                    }
                }
                if (last && pass && ht < NGO) st_ll(g_go + ht * 8 + qd, 0u, 0u, 0u, flag);
                TP(6);
                const float M = warp_max(fmaxf(fmaxf(fmaxf(__uint_as_float(hd[0].x), __uint_as_float(hd[1].x)),
                                               fmaxf(__uint_as_float(hd[2].x), __uint_as_float(hd[3].x))), __uint_as_float(hd[4].x)));
                float a[8];
#pragma unroll
                for (int i = 0; i < 8; i++) a[i] = 0.f;
#pragma unroll
                for (int s = 0; s < 5; s++) {
                    const float wgt = ex2((__uint_as_float(hd[s].x) - M) * LOG2E);
                    a[0] = fmaf(wgt, __uint_as_float(dt[s].x << 16), a[0]);
                    a[1] = fmaf(wgt, __uint_as_float(dt[s].x & 0xffff0000u), a[1]);
                    a[2] = fmaf(wgt, __uint_as_float(dt[s].y << 16), a[2]);
                    a[3] = fmaf(wgt, __uint_as_float(dt[s].y & 0xffff0000u), a[3]);
                    a[4] = fmaf(wgt, __uint_as_float(dt[s].z << 16), a[4]);
                    a[5] = fmaf(wgt, __uint_as_float(dt[s].z & 0xffff0000u), a[5]);
                    a[6] = fmaf(wgt, __uint_as_float(hd[s].y), a[6]);
                }
                {
                    const bool up16 = lane & 16, up8 = lane & 8, up4 = lane & 4;
#pragma unroll
                    for (int i = 0; i < 4; i++) a[i] = (up16 ? a[i + 4] : a[i]) + __shfl_xor_sync(0xffffffffu, up16 ? a[i] : a[i + 4], 16);
#pragma unroll
                    for (int i = 0; i < 2; i++) a[i] = (up8 ? a[i + 2] : a[i]) + __shfl_xor_sync(0xffffffffu, up8 ? a[i] : a[i + 2], 8);
                    a[0] = (up4 ? a[1] : a[0]) + __shfl_xor_sync(0xffffffffu, up4 ? a[0] : a[1], 4);
                    a[0] += __shfl_xor_sync(0xffffffffu, a[0], 2);
                    a[0] += __shfl_xor_sync(0xffffffffu, a[0], 1);
                    const float Lt = __shfl_sync(0xffffffffu, a[0], 24);
                    if (g < 6 && j == 0) obf[8 * g + hw] = __float2bfloat16(a[0] * rcp_fast(Lt));
                }
                named_bar(2, NHELP_WARPS * 32);
                TP(7);
                float yv[10];
                {
                    const uint32_t* ow = reinterpret_cast<const uint32_t*>(obf);
                    uint32_t bq[3][2];
#pragma unroll
                    for (int ks = 0; ks < 3; ks++) { bq[ks][0] = ow[8 * ks + j]; bq[ks][1] = ow[8 * ks + 4 + j]; }
                    float acc[5][4];
#pragma unroll
                    for (int i = 0; i < 5; i++) acc[i][0] = acc[i][1] = acc[i][2] = acc[i][3] = 0.f;
#pragma unroll
                    for (int ks = 0; ks < 3; ks++) {
#pragma unroll
                        for (int i = 0; i < 5; i++) mma16816(acc[i], wof[ks][i], bq[ks][0], bq[ks][1]);
                    }
#pragma unroll
                    for (int i = 0; i < 5; i++) { yv[2 * i] = acc[i][0]; yv[2 * i + 1] = acc[i][2]; }
                }
                const float y0 = j == 0 ? yv[0] : (j == 1 ? yv[3] : (j == 2 ? yv[6] : yv[9]));
                const float y1 = j == 0 ? yv[1] : (j == 1 ? yv[4] : yv[7]);
                const float y2 = j == 0 ? yv[2] : (j == 1 ? yv[5] : yv[8]);
                if (pass) {
                    if (direct) {
                        st_ll(g_y + ((bh - (NBH - NDIRECT)) * 4 + qd) * 256 + ht, __float_as_uint(y0), __float_as_uint(y1), __float_as_uint(y2), flag);
                    } else {
                        red_add_f32(hacc + b * DM + own[0], y0);
                        if (j < 3) { red_add_f32(hacc + b * DM + own[1], y1); red_add_f32(hacc + b * DM + own[2], y2); }
                    }
                }
                TP(8);
                named_bar(2, NHELP_WARPS * 32);
            }
            if (ht == 0) {
                fence_gpu();
                if (!direct) red_add_u32(&g_ycnt.v, 1u);
                asm volatile("st.relaxed.gpu.global.u32 [%0], %1;" :: "l"(reinterpret_cast<unsigned*>(g_done + bh) + qd), "r"(flag) : "memory");
            }
        }
        if (ht == 0) { TPOUT(11, 6); TPOUT(12, 7); TPOUT(4, 8); }
        if (cta >= NMLP) return;

        float hpre[3] = {0.f, 0.f, 0.f}, shift1 = 0.f;
        __nv_bfloat16* hn = reinterpret_cast<__nv_bfloat16*>(smem + OFF_HROW);
        const uint32_t* hnw = reinterpret_cast<const uint32_t*>(hn + (g & 1) * DM + 80 * hw) + j;
        float* red1 = reinterpret_cast<float*>(smem + OFF_RED1);
        uint4* const zout = g_z + (size_t)cta * DM + 80 * hw + g;
#pragma unroll 1
        for (int pass = 0; pass < 2; pass++) {
            if (pass) {
                if (ht == 0) { wait_claims((NBH - NDIRECT) * TPB - G); wait_counter(&g_ycnt.v, flag * YCNT, 200); }
                named_bar(2, NHELP_WARPS * 32);
                float h0[3];
#pragma unroll
                for (int t = 0; t < 3; t++) {
                    h0[t] = rbf(xv[0][t] + rbf(ld_relaxed_f32(hacc + own[t])));
                    hpre[t] = ld_relaxed_f32(hacc + DM + own[t]);
                }
                ln_row(h0, row_mean(h0, reinterpret_cast<float*>(stats + 16), hw, lane), hn, stats, hw, lane);
                TP(9);
#pragma unroll 1
                for (int dd = 0; dd < NDIRECT - 2; dd++) {
                    if (ht < 4) {
                        const uint4* yp = g_y + (dd * 4 + ht) * 256;
                        while (ld_ll(yp).w != flag) { __nanosleep(64); spin_check(tstart); }
                    }
                    named_bar(2, NHELP_WARPS * 32);
                    uint4 y[4];
                    const uint4* yp = g_y + dd * 1024 + ht;
#pragma unroll
                    for (int s = 0; s < 4; s++) y[s] = ld_ll(yp + s * 256);
#pragma unroll
                    for (int s = 0; s < 4; s++) {
                        while (y[s].w != flag) { y[s] = ld_ll(yp + s * 256); spin_check(tstart); }
                        hpre[0] += __uint_as_float(y[s].x); hpre[1] += __uint_as_float(y[s].y); hpre[2] += __uint_as_float(y[s].z);
                    }
                }
                {
                    const float hp1[3] = {xv[1][0] + hpre[0], xv[1][1] + hpre[1], xv[1][2] + hpre[2]};
                    named_bar(2, NHELP_WARPS * 32);
                    shift1 = row_mean(hp1, reinterpret_cast<float*>(stats + 16), hw, lane);
                }
                TP(10);
            }
            uint32_t w1f[5][4], w2f[5][4];
            if (pass) { mbar_wait(bar_w1, 0); mbar_wait(bar_w2, 0); }
#pragma unroll
            for (int i = 0; i < 5; i++) ldsm4t(w1f[i], sbase + OFF_W1 + (16 * (5 * hw + i) + krow) * 32 + mhi * 16);
#pragma unroll
            for (int i = 0; i < 5; i++) {
                const int mt = 5 * hw + i, line = krow * 10 + (mt >> 2);
                ldsm4t(w2f[i], sbase + OFF_W2 + line * 128 + (((2 * (mt & 3) + mhi) ^ (line & 7)) << 4));
            }
            if (pass) {
                if (lane < 4) { while (ld_ll(g_go + ((cta + 2 * hw) & (NGO - 1)) * 8 + lane).w != flag) spin_check(tstart); }
                __syncwarp();
                busy_until(clock64() + YWAIT);
            }
            TP(0);
            uint4 y[8];
            const uint4* yp = g_y + (NDIRECT - 2) * 1024 + ht;
#pragma unroll
            for (int s = 0; s < 8; s++) y[s] = make_uint4(0u, 0u, 0u, pass ? flag - 1u : flag);
            while (true) {
                bool ok = true;
#pragma unroll
                for (int s = 0; s < 8; s++) if (y[s].w != flag) y[s] = ld_ll(yp + s * 256);
#pragma unroll
                for (int s = 0; s < 8; s++) ok = ok && y[s].w == flag;
                if (ok) break;
                spin_check(tstart);
            }
            float v[3];
            {
                float a0 = hpre[0], a1 = hpre[1], a2 = hpre[2], b0 = 0.f, b1 = 0.f, b2 = 0.f;
#pragma unroll
                for (int s = 0; s < 4; s++) {
                    a0 += __uint_as_float(y[s].x); a1 += __uint_as_float(y[s].y); a2 += __uint_as_float(y[s].z);
                    b0 += __uint_as_float(y[4 + s].x); b1 += __uint_as_float(y[4 + s].y); b2 += __uint_as_float(y[4 + s].z);
                }
                v[0] = rbf(xv[1][0] + rbf(a0 + b0)); v[1] = rbf(xv[1][1] + rbf(a1 + b1)); v[2] = rbf(xv[1][2] + rbf(a2 + b2));
            }
            TP(1);
            ln_row(v, shift1, hn + DM, stats + 8, hw, lane);
            TP(2);
            float acc0[4] = {0.f, 0.f, 0.f, 0.f}, acc1[4] = {0.f, 0.f, 0.f, 0.f};
#pragma unroll
            for (int i = 0; i < 5; i++) {
                const uint32_t b0 = hnw[8 * i], b1 = hnw[8 * i + 4];
                if (i & 1) mma16816(acc1, w1f[i], b0, b1); else mma16816(acc0, w1f[i], b0, b1);
            }
            if (j == 0) {
                red1[hw * 32 + g] = acc0[0] + acc1[0]; red1[hw * 32 + 16 + g] = acc0[1] + acc1[1];
                red1[hw * 32 + 8 + g] = acc0[2] + acc1[2]; red1[hw * 32 + 16 + 8 + g] = acc0[3] + acc1[3];
            }
            named_bar(2, NHELP_WARPS * 32);
            TP(3);
            uint32_t b0, b1;
            {
                const float* rp = red1 + (g & 1) * 16 + 2 * j;
                float2 p[8], q[8];
#pragma unroll
                for (int k = 0; k < 8; k++) { p[k] = *reinterpret_cast<const float2*>(rp + k * 32); q[k] = *reinterpret_cast<const float2*>(rp + k * 32 + 8); }
                const float lx = ((p[0].x + p[1].x) + (p[2].x + p[3].x)) + ((p[4].x + p[5].x) + (p[6].x + p[7].x));
                const float ly = ((p[0].y + p[1].y) + (p[2].y + p[3].y)) + ((p[4].y + p[5].y) + (p[6].y + p[7].y));
                const float hx = ((q[0].x + q[1].x) + (q[2].x + q[3].x)) + ((q[4].x + q[5].x) + (q[6].x + q[7].x));
                const float hy = ((q[0].y + q[1].y) + (q[2].y + q[3].y)) + ((q[4].y + q[5].y) + (q[6].y + q[7].y));
                b0 = pack_bf16(fmaxf(lx, 0.f), fmaxf(ly, 0.f));
                b1 = pack_bf16(fmaxf(hx, 0.f), fmaxf(hy, 0.f));
            }
            TP(4);
            float z[5][4];
#pragma unroll
            for (int i = 0; i < 5; i++) { z[i][0] = z[i][1] = z[i][2] = z[i][3] = 0.f; mma16816(z[i], w2f[i], b0, b1); }
            {
                const bool j1 = j & 1, j2 = j & 2;
                const float za0 = j2 ? (j1 ? z[1][2] : z[1][0]) : (j1 ? z[0][2] : z[0][0]), zb0 = j2 ? (j1 ? z[1][3] : z[1][1]) : (j1 ? z[0][3] : z[0][1]);
                const float za1 = j2 ? (j1 ? z[3][2] : z[3][0]) : (j1 ? z[2][2] : z[2][0]), zb1 = j2 ? (j1 ? z[3][3] : z[3][1]) : (j1 ? z[2][3] : z[2][1]);
                const float za2 = j1 ? z[4][2] : z[4][0], zb2 = j1 ? z[4][3] : z[4][1];
                if (pass) {
                    st_ll(zout + 8 * j, __float_as_uint(za0), __float_as_uint(zb0), 0u, flag);
                    st_ll(zout + 8 * (4 + j), __float_as_uint(za1), __float_as_uint(zb1), 0u, flag);
                    if (j < 2) st_ll(zout + 8 * (8 + j), __float_as_uint(za2), __float_as_uint(zb2), 0u, flag);
                }
            }
            TP(5);
            if (!pass) named_bar(2, NHELP_WARPS * 32);
        }
        if (ht == 0) { TPOUT(16, 0); TPOUT(17, 1); TPOUT(18, 2); TPOUT(19, 3); TPOUT(20, 4); TPOUT(21, 5); TPOUT(5, 9); TPOUT(6, 10); }
    }
}

typedef CUresult (*EncodeTiledFn)(CUtensorMap*, CUtensorMapDataType, cuuint32_t, void*, const cuuint64_t*, const cuuint64_t*,
                                  const cuuint32_t*, const cuuint32_t*, CUtensorMapInterleave, CUtensorMapSwizzle,
                                  CUtensorMapL2promotion, CUtensorMapFloatOOBfill);

static void make_map_kv(EncodeTiledFn enc, CUtensorMap* tm, const void* base) {
    cuuint64_t dims[2] = {64, (cuuint64_t)NBH * SK * 3};
    cuuint64_t strides[1] = {128};
    cuuint32_t box[2] = {64, 192};
    cuuint32_t es[2] = {1, 1};
    enc(tm, CU_TENSOR_MAP_DATA_TYPE_BFLOAT16, 2, const_cast<void*>(base), dims, strides, box, es,
        CU_TENSOR_MAP_INTERLEAVE_NONE, CU_TENSOR_MAP_SWIZZLE_128B, CU_TENSOR_MAP_L2_PROMOTION_NONE, CU_TENSOR_MAP_FLOAT_OOB_FILL_NONE);
}
static void make_map3(EncodeTiledFn enc, CUtensorMap* tm, const void* base, uint64_t rows, uint32_t box_rows) {
    cuuint64_t dims[3] = {64, 10, rows};
    cuuint64_t strides[2] = {128, DM * 2};
    cuuint32_t box[3] = {64, 10, box_rows};
    cuuint32_t es[3] = {1, 1, 1};
    enc(tm, CU_TENSOR_MAP_DATA_TYPE_BFLOAT16, 3, const_cast<void*>(base), dims, strides, box, es,
        CU_TENSOR_MAP_INTERLEAVE_NONE, CU_TENSOR_MAP_SWIZZLE_128B, CU_TENSOR_MAP_L2_PROMOTION_NONE, CU_TENSOR_MAP_FLOAT_OOB_FILL_NONE);
}

}

extern "C" void kernel_launch(void* const* d_in, const int* in_sizes, int n_in, void* d_out, int out_size) {
    using namespace fused;
    (void)in_sizes; (void)n_in; (void)out_size;
    static EncodeTiledFn enc = nullptr;
    static int grid = 0;
    if (!enc) {
        void* fn = nullptr;
        cudaDriverEntryPointQueryResult qr;
        cudaGetDriverEntryPoint("cuTensorMapEncodeTiled", &fn, cudaEnableDefault, &qr);
        enc = (EncodeTiledFn)fn;
        int dev = 0, sms = 0;
        cudaGetDevice(&dev);
        cudaDeviceGetAttribute(&sms, cudaDevAttrMultiProcessorCount, dev);
        grid = sms < MAXG ? sms : MAXG;
        cudaFuncSetAttribute(fused_decode_kernel, cudaFuncAttributeMaxDynamicSharedMemorySize, SMEM_BYTES);
    }
    CUtensorMap tmK, tmV, tmWo, tmW2;
    make_map_kv(enc, &tmK, d_in[1]);
    make_map_kv(enc, &tmV, d_in[2]);
    make_map3(enc, &tmWo, d_in[4], NH * DH, 48);
    make_map3(enc, &tmW2, d_in[7], DFF, 16);
    fused_decode_kernel<<<grid, NTHREADS, SMEM_BYTES>>>(tmK, tmV, tmWo, tmW2, (const char*)d_in[1], (const char*)d_in[2], (const __nv_bfloat16*)d_in[0], (const __nv_bfloat16*)d_in[3],
                                                        (const __nv_bfloat16*)d_in[6], (const __nv_bfloat16*)d_in[7], (__nv_bfloat16*)d_out);
}
```

```cpp
#include <cuda_runtime.h>
#include <cuda_bf16.h>
#include <cuda.h>
#include <stdint.h>

namespace fused {

constexpr int NB = 2, DM = 640, NH = 32, SK = 16384, DH = 192, DFF = 1536;
constexpr int TILE = 64;
constexpr int TPB = SK / TILE;
constexpr int NBH = NB * NH;
constexpr int NUNITS = NBH * TPB;
constexpr int TILE_BYTES = TILE * DH * 2;
constexpr int NS = 5;
constexpr int NSX = 6;
constexpr int MAXG = 132;
constexpr int NROLE = 128;
constexpr int NMLP = 96;
constexpr int NFIN = 80;
constexpr int NEARLY = 36;
constexpr int NDIRECT = 4;
constexpr int YCNT = NROLE * NB - 4 * NDIRECT;
constexpr int NGO = 16;
constexpr int PSLOTS = 8;

#define MERGE_MARGIN 3
#define YWAIT 600
#define ZWAIT 3500

constexpr int NCONS_WARPS = 4;
constexpr int NHELP_WARPS = 8;
constexpr int NTHREADS = (NCONS_WARPS + NHELP_WARPS + 1) * 32;

constexpr int OFF_RING = 0;
constexpr int OFF_W1 = OFF_RING + NS * TILE_BYTES;
constexpr int OFF_W2 = OFF_W1 + 20480;
constexpr int OFF_WQO = OFF_W2 + 20480;
constexpr int OFF_MISC = OFF_WQO + 61440;
constexpr int OFF_HROW2 = OFF_RING + NSX * TILE_BYTES;
constexpr int OFF_RED_Q = OFF_HROW2 + 5120;
constexpr int OFF_QRAW = OFF_MISC;
constexpr int OFF_DONE = OFF_QRAW + 2048;
constexpr int OFF_HROW = OFF_DONE + 64;
constexpr int OFF_RED1 = OFF_HROW + 2560;
constexpr int OFF_SBUF = OFF_RED1 + 1024;
constexpr int OFF_STATS = OFF_SBUF + 512;
constexpr int OFF_FRED = OFF_STATS + 192;
constexpr int OFF_OBF = OFF_FRED + 384;
constexpr int OFF_META = OFF_OBF + 128;
constexpr int OFF_EPOCH = OFF_META + 32;
constexpr int OFF_BARS = OFF_EPOCH + 16;
constexpr int NBARS = 2 * NSX + 5;
constexpr int SMEM_BYTES = OFF_BARS + NBARS * 8 + 8;
static_assert(SMEM_BYTES <= 232448, "smem");
static_assert(OFF_RED_Q + 9 * 96 * 4 <= OFF_WQO, "q scratch");
static_assert(OFF_EPOCH % 16 == 0 && OFF_W2 % 1024 == 0 && OFF_WQO % 1024 == 0, "align");

constexpr float SM_SCALE = 0.07216878364870322f;
constexpr float LOG2E = 1.4426950408889634f;
constexpr float LN_EPS = 1e-5f;

struct __align__(128) Counter64 { unsigned long long v; unsigned long long pad[15]; };
struct __align__(128) Counter32 { unsigned v; unsigned pad[31]; };
__device__ Counter64 g_claim;
__device__ Counter32 g_ycnt;
__device__ Counter32 g_epoch;
__device__ __align__(128) uint4 g_qll[NBH * 32];
__device__ __align__(128) uint4 g_hdr[PSLOTS * MAXG];
__device__ __align__(128) uint4 g_done[NBH];
__device__ __align__(128) uint4 g_dat[PSLOTS * 4 * 8 * MAXG];
__device__ __align__(128) float g_hacc[2][NB * DM];
__device__ __align__(128) uint4 g_y[NDIRECT * 4 * 256];
__device__ __align__(128) uint4 g_go[NGO * 8];
__device__ __align__(128) uint4 g_z[NMLP * DM];

#define TPDECL(n) do { } while (0)
#define TP(i) do { } while (0)
#define TPOUT(slot, i) do { } while (0)
#define PROF(slot) do { } while (0)
#define PROF_REF() do { } while (0)
#define PROF_REF2() do { } while (0)

__device__ __forceinline__ uint32_t smem_u32(const void* p) { return (uint32_t)__cvta_generic_to_shared(p); }
__device__ __forceinline__ void mbar_init(uint32_t bar, uint32_t cnt) {
    asm volatile("mbarrier.init.shared::cta.b64 [%0], %1;" :: "r"(bar), "r"(cnt) : "memory");
}
__device__ __forceinline__ void mbar_expect_tx(uint32_t bar, uint32_t bytes) {
    asm volatile("mbarrier.arrive.expect_tx.shared::cta.b64 _, [%0], %1;" :: "r"(bar), "r"(bytes) : "memory");
}
__device__ __forceinline__ void mbar_arrive(uint32_t bar) {
    asm volatile("mbarrier.arrive.shared::cta.b64 _, [%0];" :: "r"(bar) : "memory");
}
__device__ __forceinline__ bool mbar_try(uint32_t bar, uint32_t parity) {
    uint32_t ok;
    asm volatile("{\n.reg .pred p;\nmbarrier.try_wait.parity.shared::cta.b64 p, [%1], %2;\nselp.u32 %0, 1, 0, p;\n}"
                 : "=r"(ok) : "r"(bar), "r"(parity) : "memory");
    return ok != 0;
}
constexpr long long SPIN_LIMIT = 4000000000LL;
__device__ __forceinline__ void spin_check(long long t0) { if (clock64() - t0 > SPIN_LIMIT) __trap(); }
__device__ __forceinline__ void busy_until(long long t) { while (clock64() < t) { } }
__device__ __forceinline__ void mbar_wait(uint32_t bar, uint32_t parity) {
    if (mbar_try(bar, parity)) return;
    const long long t0 = clock64();
    while (!mbar_try(bar, parity)) spin_check(t0);
}
__device__ __forceinline__ void tma2d_hint(uint32_t dst, const CUtensorMap* tm, int c0, int c1, uint32_t bar, uint64_t pol) {
    asm volatile("cp.async.bulk.tensor.2d.shared::cluster.global.mbarrier::complete_tx::bytes.L2::cache_hint [%0], [%1, {%3, %4}], [%2], %5;"
                 :: "r"(dst), "l"(tm), "r"(bar), "r"(c0), "r"(c1), "l"(pol) : "memory");
}
__device__ __forceinline__ void tma3d_hint(uint32_t dst, const CUtensorMap* tm, int c0, int c1, int c2, uint32_t bar, uint64_t pol) {
    asm volatile("cp.async.bulk.tensor.3d.shared::cluster.global.mbarrier::complete_tx::bytes.L2::cache_hint [%0], [%1, {%3, %4, %5}], [%2], %6;"
                 :: "r"(dst), "l"(tm), "r"(bar), "r"(c0), "r"(c1), "r"(c2), "l"(pol) : "memory");
}
__device__ __forceinline__ void fence_proxy_async() { asm volatile("fence.proxy.async;" ::: "memory"); }
__device__ __forceinline__ void named_bar(int id, int nthreads) {
    asm volatile("bar.sync %0, %1;" :: "r"(id), "r"(nthreads) : "memory");
}
__device__ __forceinline__ void ldsm4(uint32_t (&r)[4], uint32_t addr) {
    asm volatile("ldmatrix.sync.aligned.m8n8.x4.shared.b16 {%0,%1,%2,%3}, [%4];"
                 : "=r"(r[0]), "=r"(r[1]), "=r"(r[2]), "=r"(r[3]) : "r"(addr) : "memory");
}
__device__ __forceinline__ void ldsm4t(uint32_t (&r)[4], uint32_t addr) {
    asm volatile("ldmatrix.sync.aligned.m8n8.x4.trans.shared.b16 {%0,%1,%2,%3}, [%4];"
                 : "=r"(r[0]), "=r"(r[1]), "=r"(r[2]), "=r"(r[3]) : "r"(addr) : "memory");
}
__device__ __forceinline__ void mma16816(float (&c)[4], const uint32_t (&a)[4], uint32_t b0, uint32_t b1) {
    asm volatile("mma.sync.aligned.m16n8k16.row.col.f32.bf16.bf16.f32 {%0,%1,%2,%3}, {%4,%5,%6,%7}, {%8,%9}, {%0,%1,%2,%3};"
                 : "+f"(c[0]), "+f"(c[1]), "+f"(c[2]), "+f"(c[3])
                 : "r"(a[0]), "r"(a[1]), "r"(a[2]), "r"(a[3]), "r"(b0), "r"(b1));
}
__device__ __forceinline__ uint32_t pack_bf16(float lo, float hi) {
    uint32_t r;
    asm("cvt.rn.bf16x2.f32 %0, %1, %2;" : "=r"(r) : "f"(hi), "f"(lo));
    return r;
}
__device__ __forceinline__ float rbf(float x) { return __uint_as_float(pack_bf16(0.f, x) & 0xffff0000u); }
__device__ __forceinline__ float sqrt_fast(float x) { float y; asm("sqrt.approx.f32 %0, %1;" : "=f"(y) : "f"(x)); return y; }
__device__ __forceinline__ float rcp_fast(float x) { float y; asm("rcp.approx.f32 %0, %1;" : "=f"(y) : "f"(x)); return y; }
__device__ __forceinline__ float ex2(float x) { float y; asm("ex2.approx.ftz.f32 %0, %1;" : "=f"(y) : "f"(x)); return y; }
__device__ __forceinline__ void st_ll(uint4* p, uint32_t a, uint32_t b, uint32_t c, uint32_t d) {
    unsigned long long lo = (unsigned long long)a | ((unsigned long long)b << 32);
    unsigned long long hi = (unsigned long long)c | ((unsigned long long)d << 32);
    asm volatile("{\n.reg .b128 t;\nmov.b128 t, {%1, %2};\nst.relaxed.gpu.global.b128 [%0], t;\n}" :: "l"(p), "l"(lo), "l"(hi) : "memory");
}
__device__ __forceinline__ uint4 ld_ll(const uint4* p) {
    unsigned long long lo, hi;
    asm volatile("{\n.reg .b128 t;\nld.relaxed.gpu.global.b128 t, [%2];\nmov.b128 {%0, %1}, t;\n}" : "=l"(lo), "=l"(hi) : "l"(p) : "memory");
    uint4 r; r.x = (uint32_t)lo; r.y = (uint32_t)(lo >> 32); r.z = (uint32_t)hi; r.w = (uint32_t)(hi >> 32);
    return r;
}
__device__ __forceinline__ unsigned ld_relaxed_u32(const unsigned* p) {
    unsigned v; asm volatile("ld.relaxed.gpu.global.u32 %0, [%1];" : "=r"(v) : "l"(p) : "memory"); return v;
}
__device__ __forceinline__ unsigned long long ld_relaxed_u64(const unsigned long long* p) {
    unsigned long long v; asm volatile("ld.relaxed.gpu.global.u64 %0, [%1];" : "=l"(v) : "l"(p) : "memory"); return v;
}
__device__ __forceinline__ float ld_relaxed_f32(const float* p) {
    float v; asm volatile("ld.relaxed.gpu.global.f32 %0, [%1];" : "=f"(v) : "l"(p) : "memory"); return v;
}
__device__ __forceinline__ void fence_gpu() { asm volatile("fence.acq_rel.gpu;" ::: "memory"); }
__device__ __forceinline__ void red_add_u32(unsigned* p, unsigned v) {
    asm volatile("red.relaxed.gpu.global.add.u32 [%0], %1;" :: "l"(p), "r"(v) : "memory");
}
__device__ __forceinline__ void red_add_f32(float* p, float v) {
    asm volatile("red.relaxed.gpu.global.add.f32 [%0], %1;" :: "l"(p), "f"(v) : "memory");
}
__device__ __forceinline__ void wait_counter(const unsigned* p, unsigned target, unsigned sleep_ns) {
    const long long t0 = clock64();
    while (true) {
        unsigned v;
        asm volatile("ld.acquire.gpu.global.u32 %0, [%1];" : "=r"(v) : "l"(p) : "memory");
        if ((int)(v - target) >= 0) break;
        __nanosleep(sleep_ns); spin_check(t0);
    }
}
__device__ __forceinline__ void cp_async16(uint32_t dst, const void* src) {
    asm volatile("cp.async.cg.shared.global [%0], [%1], 16;" :: "r"(dst), "l"(src) : "memory");
}
__device__ __forceinline__ void cp_async16_hint(uint32_t dst, const void* src, uint64_t pol) {
    asm volatile("cp.async.cg.shared.global.L2::cache_hint [%0], [%1], 16, %2;" :: "r"(dst), "l"(src), "l"(pol) : "memory");
}
__device__ __forceinline__ uint64_t policy_evict_first() {
    uint64_t pol;
    asm volatile("createpolicy.fractional.L2::evict_first.b64 %0, 1.0;" : "=l"(pol));
    return pol;
}
__device__ __forceinline__ void cp_async_commit() { asm volatile("cp.async.commit_group;" ::: "memory"); }
__device__ __forceinline__ void cp_async_wait_all() { asm volatile("cp.async.wait_all;" ::: "memory"); }
__device__ __forceinline__ uint4 lds128(uint32_t addr) {
    uint4 r;
    asm volatile("ld.shared.v4.u32 {%0,%1,%2,%3}, [%4];" : "=r"(r.x), "=r"(r.y), "=r"(r.z), "=r"(r.w) : "r"(addr) : "memory");
    return r;
}
__device__ __forceinline__ void sts128(uint32_t addr, uint4 v) {
    asm volatile("st.shared.v4.u32 [%0], {%1,%2,%3,%4};" :: "r"(addr), "r"(v.x), "r"(v.y), "r"(v.z), "r"(v.w) : "memory");
}
__device__ __forceinline__ float warp_max(float v) {
    int i = __float_as_int(v);
    i ^= (i >> 31) & 0x7fffffff;
    i = __reduce_max_sync(0xffffffffu, i);
    i ^= (i >> 31) & 0x7fffffff;
    return __int_as_float(i);
}

__device__ __forceinline__ void ln_row(const float (&v)[3], float c, __nv_bfloat16* hn, float2* stats, int hw, int lane) {
    const int g = lane >> 2, j = lane & 3;
    const bool full = j < 3;
    const float d0 = v[0] - c, d1 = full ? v[1] - c : 0.f, d2 = full ? v[2] - c : 0.f;
    float s1 = (d0 + d1) + d2, s2 = fmaf(d0, d0, fmaf(d1, d1, d2 * d2));
#pragma unroll
    for (int o = 16; o >= 1; o >>= 1) { s1 += __shfl_xor_sync(0xffffffffu, s1, o); s2 += __shfl_xor_sync(0xffffffffu, s2, o); }
    if (lane == 0) stats[hw] = make_float2(s1, s2);
    named_bar(2, NHELP_WARPS * 32);
    const float4* sp = reinterpret_cast<const float4*>(stats);
    const float4 a = sp[0], b = sp[1], cc = sp[2], d = sp[3];
    const float S1 = (((a.x + a.z) + (b.x + b.z)) + ((cc.x + cc.z) + (d.x + d.z))) * (1.0f / DM);
    const float S2 = (((a.y + a.w) + (b.y + b.w)) + ((cc.y + cc.w) + (d.y + d.w))) * (1.0f / DM);
    const float mb = rbf(c + S1);
    const float rinv = rcp_fast(rbf(sqrt_fast(rbf(rbf(fmaxf(fmaf(-S1, S1, S2), 0.f)) + LN_EPS))));
    __nv_bfloat16* hp = hn + 80 * hw + 24 * j + g;
    hp[0] = __float2bfloat16(rbf(v[0] - mb) * rinv);
    if (full) { hp[8] = __float2bfloat16(rbf(v[1] - mb) * rinv); hp[16] = __float2bfloat16(rbf(v[2] - mb) * rinv); }
    __syncwarp();
}
__device__ __forceinline__ float row_mean(const float (&v)[3], float* st8, int hw, int lane) {
    const bool full = (lane & 3) < 3;
    float s1 = v[0] + (full ? v[1] + v[2] : 0.f);
#pragma unroll
    for (int o = 16; o >= 1; o >>= 1) s1 += __shfl_xor_sync(0xffffffffu, s1, o);
    if (lane == 0) st8[hw] = s1;
    named_bar(2, NHELP_WARPS * 32);
    const float4 a = *reinterpret_cast<const float4*>(st8), b = *reinterpret_cast<const float4*>(st8 + 4);
    return (((a.x + a.y) + (a.z + a.w)) + ((b.x + b.y) + (b.z + b.w))) * (1.0f / DM);
}

__device__ __forceinline__ void ln_rows2(const float (&v)[2][3], float* hrow2, float4* stats, int hw, int lane, uint32_t (&fr)[5][2]) {
    const int g = lane >> 2, j = lane & 3;
    const bool full = j < 3;
    float* hp = hrow2 + 80 * hw + 24 * j + g;
    hp[0] = v[0][0]; hp[DM] = v[1][0];
    if (full) { hp[8] = v[0][1]; hp[16] = v[0][2]; hp[DM + 8] = v[1][1]; hp[DM + 16] = v[1][2]; }
    float c[2], s1[2], s2[2];
#pragma unroll
    for (int r = 0; r < 2; r++) {
        c[r] = __shfl_sync(0xffffffffu, v[r][0], 0);
        const float d0 = v[r][0] - c[r], d1 = full ? v[r][1] - c[r] : 0.f, d2 = full ? v[r][2] - c[r] : 0.f;
        s1[r] = d0 + d1 + d2; s2[r] = d0 * d0 + d1 * d1 + d2 * d2;
    }
#pragma unroll
    for (int o = 16; o >= 1; o >>= 1) {
#pragma unroll
        for (int r = 0; r < 2; r++) { s1[r] += __shfl_xor_sync(0xffffffffu, s1[r], o); s2[r] += __shfl_xor_sync(0xffffffffu, s2[r], o); }
    }
    if (lane == 0) stats[hw] = make_float4(c[0] + s1[0] * (1.0f / 80.0f), s2[0] - s1[0] * s1[0] * (1.0f / 80.0f),
                                           c[1] + s1[1] * (1.0f / 80.0f), s2[1] - s1[1] * s1[1] * (1.0f / 80.0f));
    named_bar(2, NHELP_WARPS * 32);
    const int row = g & 1;
    const float2* sp = reinterpret_cast<const float2*>(stats) + row;
    float mw[8], m2 = 0.f, mean = 0.f;
#pragma unroll
    for (int k = 0; k < 8; k++) { const float2 t = sp[2 * k]; mw[k] = t.x; mean += t.x; m2 += t.y; }
    mean *= 0.125f;
    float dev = 0.f;
#pragma unroll
    for (int k = 0; k < 8; k++) dev += (mw[k] - mean) * (mw[k] - mean);
    const float mb = rbf(mean);
    const float rinv = rcp_fast(rbf(sqrt_fast(rbf(rbf(fmaxf(m2 + 80.0f * dev, 0.f) * (1.0f / DM)) + LN_EPS))));
    const float* fp = hrow2 + row * DM + 80 * hw + 2 * j;
#pragma unroll
    for (int i = 0; i < 5; i++) {
        const float2 p = *reinterpret_cast<const float2*>(fp + 16 * i);
        const float2 q = *reinterpret_cast<const float2*>(fp + 16 * i + 8);
        fr[i][0] = (g < 2) ? pack_bf16(rbf(p.x - mb) * rinv, rbf(p.y - mb) * rinv) : 0u;
        fr[i][1] = (g < 2) ? pack_bf16(rbf(q.x - mb) * rinv, rbf(q.y - mb) * rinv) : 0u;
    }
}

__global__ void __launch_bounds__(NTHREADS, 1)
fused_decode_kernel(const __grid_constant__ CUtensorMap tmK, const __grid_constant__ CUtensorMap tmV,
                    const __grid_constant__ CUtensorMap tmWo, const __grid_constant__ CUtensorMap tmW2,
                    const char* __restrict__ kc, const char* __restrict__ vc,
                    const __nv_bfloat16* __restrict__ x, const __nv_bfloat16* __restrict__ wq,
                    const __nv_bfloat16* __restrict__ w1, const __nv_bfloat16* __restrict__ w2, __nv_bfloat16* __restrict__ out)
{
    extern __shared__ __align__(1024) unsigned char smem[];
    const uint32_t sbase = smem_u32(smem);
    const int tid = threadIdx.x, warp = tid >> 5, lane = tid & 31;
    const int cta = blockIdx.x, G = gridDim.x;

    const uint32_t bar_full = sbase + OFF_BARS;
    const uint32_t bar_empty = bar_full + NSX * 8;
    const uint32_t bar_wo = bar_empty + NSX * 8;
    const uint32_t bar_w1 = bar_wo + 8;
    const uint32_t bar_w2 = bar_w1 + 8;
    const uint32_t bar_cdone = bar_w2 + 8;
    const uint32_t bar_qdone = bar_cdone + 8;
    volatile int* meta = reinterpret_cast<volatile int*>(smem + OFF_META);

    uint64_t pol = 0;
    const long long tstart = clock64();
    if (tid == NTHREADS - 32) {
        pol = policy_evict_first();
        asm volatile("cp.async.bulk.prefetch.L2.global.L2::cache_hint [%0], %1, %2;" :: "l"(kc + (size_t)cta * TILE_BYTES), "r"(TILE_BYTES), "l"(pol) : "memory");
        asm volatile("cp.async.bulk.prefetch.L2.global.L2::cache_hint [%0], %1, %2;" :: "l"(vc + (size_t)cta * TILE_BYTES), "r"(TILE_BYTES), "l"(pol) : "memory");
    }
    const int ht = tid - NCONS_WARPS * 32;
    auto load_wq = [&]() {
        const __nv_bfloat16* src = wq + cta * 48;
        const uint64_t wpol = policy_evict_first();
#pragma unroll
        for (int i = 0; i < 15; i++) {
            const int idx = ht + 256 * i, row = idx / 6, u = idx - 6 * row;
            cp_async16_hint(sbase + OFF_WQO + idx * 16, src + (size_t)row * (NH * DH) + u * 8, wpol);
        }
        cp_async_commit();
    };
    if (warp >= NCONS_WARPS && warp < NCONS_WARPS + NHELP_WARPS && cta < NROLE) {
        if (ht < 160) cp_async16(sbase + OFF_HROW + ht * 16, x + ht * 8);
        if (ht == 160) cp_async16(sbase + OFF_EPOCH, &g_epoch);
        cp_async_commit();
        if (cta < NEARLY) load_wq();
    }
    if (warp == NCONS_WARPS + NHELP_WARPS && lane == 0) {
        PROF(0);
        for (int i = 0; i < NSX; i++) { mbar_init(bar_full + 8 * i, 1); mbar_init(bar_empty + 8 * i, NCONS_WARPS); }
        mbar_init(bar_wo, 1); mbar_init(bar_w1, 32); mbar_init(bar_w2, 1); mbar_init(bar_cdone, NCONS_WARPS); mbar_init(bar_qdone, 1);
        asm volatile("fence.mbarrier_init.release.cluster;" ::: "memory");
        asm volatile("fence.proxy.async.shared::cta;" ::: "memory");
        meta[0] = cta;
        mbar_expect_tx(bar_full, TILE_BYTES);
        tma2d_hint(sbase + OFF_RING, &tmK, 0, cta * 192, bar_full, pol);
        mbar_expect_tx(bar_full + 8, TILE_BYTES);
        tma2d_hint(sbase + OFF_RING + TILE_BYTES, &tmV, 0, cta * 192, bar_full + 8, pol);
    }
    __syncthreads();

    if (warp == NCONS_WARPS + NHELP_WARPS) {
        asm volatile("setmaxnreg.dec.sync.aligned.u32 40;");
        if (lane == 0) {
            unsigned long long old = atomicAdd(&g_claim.v, 1ULL);
            PROF_REF();
            int slot = 2, lim = NSX; uint32_t ph = 1;
            int wslot = 0, wlim = NSX; uint32_t wph = 0;
            while (true) {
                const int unit = (int)(old & (NUNITS - 1)) + G;
                if (unit >= NUNITS) break;
                mbar_wait(bar_full + 8 * wslot, wph); if (++wslot == wlim) { wslot = 0; wph ^= 1; wlim = NS; }
                mbar_wait(bar_empty + 8 * slot, ph);
                meta[slot] = unit;
                mbar_expect_tx(bar_full + 8 * slot, TILE_BYTES);
                tma2d_hint(sbase + OFF_RING + slot * TILE_BYTES, &tmK, 0, unit * 192, bar_full + 8 * slot, pol);
                if (++slot == lim) { slot = 0; ph ^= 1; lim = NS; }
                mbar_wait(bar_full + 8 * wslot, wph); if (++wslot == wlim) { wslot = 0; wph ^= 1; wlim = NS; }
                mbar_wait(bar_empty + 8 * slot, ph);
                mbar_expect_tx(bar_full + 8 * slot, TILE_BYTES);
                tma2d_hint(sbase + OFF_RING + slot * TILE_BYTES, &tmV, 0, unit * 192, bar_full + 8 * slot, pol);
                if (++slot == lim) { slot = 0; ph ^= 1; lim = NS; }
                old = atomicAdd(&g_claim.v, 1ULL);
            }
            PROF(2);
            PROF_REF2();
            mbar_wait(bar_empty + 8 * slot, ph);
            meta[slot] = -1;
            mbar_arrive(bar_full + 8 * slot);
        }
        __syncwarp();
        if (cta < NMLP) {
            const __nv_bfloat16* src = w1 + cta * 16;
            const uint64_t wpol = policy_evict_first();
#pragma unroll 4
            for (int i = 0; i < 40; i++) {
                const int idx = lane + 32 * i;
                cp_async16_hint(sbase + OFF_W1 + idx * 16, src + (size_t)(idx >> 1) * DFF + (idx & 1) * 8, wpol);
            }
            asm volatile("cp.async.mbarrier.arrive.noinc.shared::cta.b64 [%0];" :: "r"(bar_w1) : "memory");
            if (lane == 0) {
                mbar_wait(bar_qdone, 0);
                fence_proxy_async();
                mbar_expect_tx(bar_w2, 20480);
                tma3d_hint(sbase + OFF_W2, &tmW2, 0, 0, cta * 16, bar_w2, pol);
            }
            cp_async_wait_all();
        }
    } else if (warp < NCONS_WARPS) {
        asm volatile("setmaxnreg.dec.sync.aligned.u32 96;");
        const int w = warp, g = lane >> 2, j = lane & 3;
        uint4* const dat_base = g_dat + ((size_t)w * 8 + g) * MAXG + cta;
        uint4* const hdr_base = g_hdr + cta;
        const uint32_t epoch = ld_relaxed_u32(&g_epoch.v);
        const uint32_t flag = epoch + 1u;
        uint32_t koff[3];
        {
            const int key = 16 * w + (lane & 7) + 8 * ((lane >> 3) & 1), hi = lane >> 4;
#pragma unroll
            for (int c = 0; c < 3; c++) { const int r = key * 3 + c; koff[c] = r * 128 + (((r & 7) ^ hi) << 4); }
        }
        uint32_t voff[3];
        {
            const int key = (lane & 7) + 8 * (lane >> 4), hi = (lane >> 3) & 1;
#pragma unroll
            for (int mt = 0; mt < 3; mt++) {
                const int U = 6 * w + 2 * mt + hi, c = U >> 3, u = U & 7, r = key * 3 + c;
                voff[mt] = r * 128 + ((u ^ (r & 7)) << 4);
            }
        }
        const bool act = (g >> 1) == j;
        const uint32_t sel0 = act ? ((g & 1) ? 0x1044u : 0x4410u) : 0x4444u;
        const uint32_t sel1 = act ? ((g & 1) ? 0x3244u : 0x4432u) : 0x4444u;
        float* sbuf = reinterpret_cast<float*>(smem + OFF_SBUF);
        const uint32_t qraw = sbase + OFF_QRAW + w * 512;
        const uint32_t dnraw = sbase + OFF_DONE + w * 16;

        uint32_t qf[24];
        float o[3][4];
        float m_run = -INFINITY, l_run = 0.f;
        int cur_bh = -1, pre_bh = -1, done_bh = -1, par = 0;
        int slot = 0, lim = NSX; uint32_t ph = 0;

        auto advance_to = [&](int nb) {
#pragma unroll 1
            while (cur_bh < nb) {
                if (cur_bh >= 0) {
                    if (cur_bh >= PSLOTS) {
                        uint4 dn = lds128(dnraw);
                        if (done_bh != cur_bh - PSLOTS || dn.x != flag || dn.y != flag || dn.z != flag || dn.w != flag) {
                            const long long t0 = clock64();
                            do { dn = ld_ll(g_done + cur_bh - PSLOTS); spin_check(t0); } while (dn.x != flag || dn.y != flag || dn.z != flag || dn.w != flag);
                        }
                    }
                    const uint32_t tag = flag * 8u + (uint32_t)(cur_bh >> 3);
                    float lo[3], hi[3];
#pragma unroll
                    for (int mt = 0; mt < 3; mt++) {
                        lo[mt] = o[mt][0] + o[mt][1]; hi[mt] = o[mt][2] + o[mt][3];
                        lo[mt] += __shfl_xor_sync(0xffffffffu, lo[mt], 1); hi[mt] += __shfl_xor_sync(0xffffffffu, hi[mt], 1);
                        lo[mt] += __shfl_xor_sync(0xffffffffu, lo[mt], 2); hi[mt] += __shfl_xor_sync(0xffffffffu, hi[mt], 2);
                    }
                    if (j == 0)
                        st_ll(dat_base + (cur_bh & (PSLOTS - 1)) * (4 * 8 * MAXG), pack_bf16(lo[0], hi[0]), pack_bf16(lo[1], hi[1]), pack_bf16(lo[2], hi[2]), tag);
                    if (w == 0) {
                        float l = l_run;
                        l += __shfl_xor_sync(0xffffffffu, l, 4);
                        l += __shfl_xor_sync(0xffffffffu, l, 8);
                        l += __shfl_xor_sync(0xffffffffu, l, 16);
                        if (lane == 1) st_ll(hdr_base + (cur_bh & (PSLOTS - 1)) * MAXG, __float_as_uint(m_run), __float_as_uint(l), 0u, tag);
                    }
                }
                m_run = -INFINITY; l_run = 0.f;
#pragma unroll
                for (int mt = 0; mt < 3; mt++) { o[mt][0] = o[mt][1] = o[mt][2] = o[mt][3] = 0.f; }
                cur_bh++;
            }
        };

        {
            if (w == 0) {
                const long long t0 = clock64();
                const uint4* qp = g_qll + lane;
                uint4 r0 = ld_ll(qp);
                while (!__all_sync(0xffffffffu, r0.w == flag)) { __nanosleep(200); r0 = ld_ll(qp); spin_check(t0); }
#pragma unroll
                for (int k = 0; k < NCONS_WARPS; k++) sts128(sbase + OFF_QRAW + k * 512 + lane * 16, r0);
            }
            named_bar(1, NCONS_WARPS * 32);
            pre_bh = 0;
            if (w == 0 && lane == 0) PROF(1);
        }

        while (true) {
            mbar_wait(bar_full + 8 * slot, ph);
            const int unit = meta[slot];
            if (unit < 0) break;
            const int bh = unit >> 8;
            if (bh != cur_bh) {
                cp_async_wait_all();
                __syncwarp();
                advance_to(bh);
                bool have = false;
                if (pre_bh == bh) {
                    bool ok = true;
#pragma unroll
                    for (int t = 0; t < 8; t++) {
                        const uint4 r = lds128(qraw + (j * 8 + t) * 16);
                        qf[3 * t] = r.x; qf[3 * t + 1] = r.y; qf[3 * t + 2] = r.z;
                        ok = ok && (r.w == flag);
                    }
                    have = __all_sync(0xffffffffu, ok);
                }
                if (!have) {
                    const long long t0 = clock64();
                    const uint4* qp = g_qll + bh * 32 + lane;
                    uint4 r0 = ld_ll(qp);
                    while (!__all_sync(0xffffffffu, r0.w == flag)) { __nanosleep(200); r0 = ld_ll(qp); spin_check(t0); }
                    sts128(qraw + lane * 16, r0);
                    __syncwarp();
#pragma unroll
                    for (int t = 0; t < 8; t++) {
                        const uint4 r = lds128(qraw + (j * 8 + t) * 16);
                        qf[3 * t] = r.x; qf[3 * t + 1] = r.y; qf[3 * t + 2] = r.z;
                    }
                }
                __syncwarp();
                pre_bh = bh + 1;
                if (pre_bh < NBH) cp_async16(qraw + lane * 16, g_qll + pre_bh * 32 + lane);
                done_bh = bh - PSLOTS;
                if (done_bh >= 0 && lane == 0) cp_async16(dnraw, g_done + done_bh);
            }
            float s0[4] = {0.f, 0.f, 0.f, 0.f}, s1[4] = {0.f, 0.f, 0.f, 0.f}, s2[4] = {0.f, 0.f, 0.f, 0.f};
            {
                const uint32_t kb = sbase + OFF_RING + slot * TILE_BYTES;
#pragma unroll
                for (int i = 0; i < 4; i++) {
                    uint32_t a[4], b[4], c[4];
                    ldsm4(a, kb + (koff[0] ^ (i * 32)));
                    ldsm4(b, kb + (koff[1] ^ (i * 32)));
                    ldsm4(c, kb + (koff[2] ^ (i * 32)));
                    mma16816(s0, a, qf[2 * i], qf[2 * i + 1]);
                    mma16816(s1, b, qf[8 + 2 * i], qf[8 + 2 * i + 1]);
                    mma16816(s2, c, qf[16 + 2 * i], qf[16 + 2 * i + 1]);
                }
            }
            const float slo = rbf(rbf(s0[0] + s1[0] + s2[0]) * SM_SCALE), shi = rbf(rbf(s0[2] + s1[2] + s2[2]) * SM_SCALE);
            __syncwarp();
            if (lane == 0) mbar_arrive(bar_empty + 8 * slot);
            if (++slot == lim) { slot = 0; ph ^= 1; lim = NS; }
            float* sb = sbuf + par * 64;
            if (j == 0) { sb[16 * w + g] = slo; sb[16 * w + 8 + g] = shi; }
            par ^= 1;
            named_bar(1, NCONS_WARPS * 32);
            float sv[8];
#pragma unroll
            for (int kk = 0; kk < 4; kk++) { sv[2 * kk] = sb[16 * kk + g]; sv[2 * kk + 1] = sb[16 * kk + 8 + g]; }
            float mx = fmaxf(fmaxf(fmaxf(sv[0], sv[1]), fmaxf(sv[2], sv[3])), fmaxf(fmaxf(sv[4], sv[5]), fmaxf(sv[6], sv[7])));
            mx = warp_max(mx);
            const float m_new = fmaxf(m_run, mx);
            const float mc = m_new * LOG2E;
            const float alpha = ex2(m_run * LOG2E - mc);
            m_run = m_new;
            uint32_t pb[4][2];
            float psum = 0.f;
#pragma unroll
            for (int kk = 0; kk < 4; kk++) {
                const float p0 = ex2(fmaf(sv[2 * kk], LOG2E, -mc));
                const float p1 = ex2(fmaf(sv[2 * kk + 1], LOG2E, -mc));
                psum += p0 + p1;
                const uint32_t pk = pack_bf16(p0, p1);
                pb[kk][0] = __byte_perm(pk, 0u, sel0);
                pb[kk][1] = __byte_perm(pk, 0u, sel1);
            }
            l_run = l_run * alpha + psum;
#pragma unroll
            for (int mt = 0; mt < 3; mt++) { o[mt][0] *= alpha; o[mt][1] *= alpha; o[mt][2] *= alpha; o[mt][3] *= alpha; }
            mbar_wait(bar_full + 8 * slot, ph);
            {
                const uint32_t vb = sbase + OFF_RING + slot * TILE_BYTES;
#pragma unroll
                for (int k2 = 0; k2 < 4; k2 += 2) {
                    uint32_t a[2][3][4];
#pragma unroll
                    for (int kk = 0; kk < 2; kk++)
#pragma unroll
                        for (int mt = 0; mt < 3; mt++) ldsm4t(a[kk][mt], vb + voff[mt] + (k2 + kk) * 6144);
#pragma unroll
                    for (int kk = 0; kk < 2; kk++)
#pragma unroll
                        for (int mt = 0; mt < 3; mt++) mma16816(o[mt], a[kk][mt], pb[k2 + kk][0], pb[k2 + kk][1]);
                }
            }
            __syncwarp();
            if (lane == 0) mbar_arrive(bar_empty + 8 * slot);
            if (++slot == lim) { slot = 0; ph ^= 1; lim = NS; }
        }
        cp_async_wait_all();
        __syncwarp();
        advance_to(NBH);
        if (lane == 0) mbar_arrive(bar_cdone);
        if (w == 0 && lane == 0) PROF(3);
        __syncwarp();
        if (cta < NFIN) {
            TPDECL(4);
            const int nn = lane & 7, sub = lane >> 3;
            const int n = 8 * cta + nn;
            const long long t0 = clock64();
            float* fred = reinterpret_cast<float*>(smem + OFF_FRED);
            const int hw2 = n / 80, r = n - 80 * hw2, idx = r >> 3, jj = idx / 3, tt = idx - 3 * jj;
            const int yoff = sub * 256 + hw2 * 32 + nn * 4 + jj;
            const uint4* zp = g_z + (size_t)(24 * w + sub) * DM + n;
            float xb = 0.f, abase = 0.f, yv = 0.f;
            if (lane < 4) { while (ld_ll(g_go + ((cta + 4 * w) & (NGO - 1)) * 8 + lane).w != flag) spin_check(t0); }
            __syncwarp();
            TP(0);
            const long long t1 = clock64();
#pragma unroll 1
            for (int pass = 0; pass < 2; pass++) {
                if (pass) {
                    if (w == 0) {
                        if (lane == 0) wait_counter(&g_ycnt.v, flag * YCNT, 100);
                        __syncwarp();
                        if (lane < 16) { xb = __bfloat162float(x[sub * DM + n]); abase = ld_relaxed_f32(g_hacc[epoch & 1] + sub * DM + n); }
                    }
                    if (w < NDIRECT) {
                        if (w == NDIRECT - 1) busy_until(t1 + YWAIT + 300);
                        const uint4* yp = g_y + w * 1024 + yoff;
                        uint4 d = ld_ll(yp);
                        while (d.w != flag) { d = ld_ll(yp); spin_check(t0); }
                        yv = __uint_as_float(tt == 0 ? d.x : (tt == 1 ? d.y : d.z));
                    }
                    busy_until(t1 + ZWAIT);
                }
                uint4 d[6];
#pragma unroll
                for (int s = 0; s < 6; s++) d[s] = make_uint4(0u, 0u, 0u, pass ? flag - 1u : flag);
                while (true) {
                    bool ok = true;
#pragma unroll
                    for (int s = 0; s < 6; s++) { if (d[s].w != flag) d[s] = ld_ll(zp + (size_t)4 * s * DM); }
#pragma unroll
                    for (int s = 0; s < 6; s++) ok = ok && d[s].w == flag;
                    if (ok) break;
                    spin_check(t0);
                }
                float z0 = 0.f, z1 = 0.f, ya = yv;
#pragma unroll
                for (int s = 0; s < 6; s++) { z0 += __uint_as_float(d[s].x); z1 += __uint_as_float(d[s].y); }
                __syncwarp();
                TP(1);
                z0 += __shfl_xor_sync(0xffffffffu, z0, 8); z1 += __shfl_xor_sync(0xffffffffu, z1, 8); ya += __shfl_xor_sync(0xffffffffu, ya, 8);
                z0 += __shfl_xor_sync(0xffffffffu, z0, 16); z1 += __shfl_xor_sync(0xffffffffu, z1, 16); ya += __shfl_xor_sync(0xffffffffu, ya, 16);
                if (lane < 8) { fred[w * 24 + nn] = z0; fred[w * 24 + 8 + nn] = z1; fred[w * 24 + 16 + nn] = ya; }
                named_bar(1, NCONS_WARPS * 32);
                if (w == 0 && lane < 16) {
                    const float mlp = (fred[lane] + fred[24 + lane]) + (fred[48 + lane] + fred[72 + lane]);
                    const float yd = (fred[16 + nn] + fred[40 + nn]) + (fred[64 + nn] + fred[88 + nn]);
                    const float h = rbf(xb + rbf(abase + (sub ? yd : 0.f)));
                    if (pass) out[sub * DM + n] = __float2bfloat16(h + rbf(mlp));
                }
                if (!pass) named_bar(1, NCONS_WARPS * 32);
            }
            TP(2);
            if (cta == 0 && w == 0 && lane == 0) g_epoch.v = epoch + 1u;
            if (w == 0 && lane == 0) { TPOUT(13, 0); TPOUT(14, 1); TPOUT(7, 2); }
        }
    } else {
        asm volatile("setmaxnreg.inc.sync.aligned.u32 144;");
        if (cta >= NROLE) return;
        const int hw = warp - NCONS_WARPS;
        const int g = lane >> 2, j = lane & 3;
        const int head = cta >> 2, qd = cta & 3;
        int own[3];
#pragma unroll
        for (int t = 0; t < 3; t++) own[t] = 80 * hw + 8 * ((j < 3) ? 3 * j + t : 9) + g;
        if (ht < 16) st_ll(g_qll + ((ht >> 3) * NH + head) * 32 + ((ht >> 1) & 3) * 8 + 2 * qd + (ht & 1), 0u, 0u, 0u, 0u);
        float xv[2][3];
        {
            if (cta < NEARLY) asm volatile("cp.async.wait_group 1;" ::: "memory"); else asm volatile("cp.async.wait_group 0;" ::: "memory");
            named_bar(2, NHELP_WARPS * 32);
            const __nv_bfloat16* xs = reinterpret_cast<const __nv_bfloat16*>(smem + OFF_HROW);
#pragma unroll
            for (int t = 0; t < 3; t++) { xv[0][t] = __bfloat162float(xs[own[t]]); xv[1][t] = __bfloat162float(xs[DM + own[t]]); }
        }
        const uint32_t epoch = *reinterpret_cast<const uint32_t*>(smem + OFF_EPOCH);
        const uint32_t flag = epoch + 1u;
        float* hacc = g_hacc[epoch & 1];
        float2* stats = reinterpret_cast<float2*>(smem + OFF_STATS);
        const int krow = (lane & 7) + 8 * (lane >> 4), mhi = (lane >> 3) & 1;
        auto wait_claims = [&](int target) {
            while (true) {
                const int rem = target - (int)(long long)(ld_relaxed_u64(&g_claim.v) - ((unsigned long long)epoch << 14));
                if (rem <= 0) break;
                const unsigned ns = rem > 2000 ? 8000u : (unsigned)rem * 4u;
                __nanosleep(ns < 64u ? 64u : ns);
                spin_check(tstart);
            }
        };
        TPDECL(12);

        {
            uint32_t bf[5][2];
            ln_rows2(xv, reinterpret_cast<float*>(smem + OFF_HROW2), reinterpret_cast<float4*>(smem + OFF_STATS), hw, lane, bf);
            if (ht == 0) PROF(8);
            if (cta >= NEARLY) load_wq();
            cp_async_wait_all();
            named_bar(2, NHELP_WARPS * 32);
            if (ht == 0) PROF(9);
            float* red = reinterpret_cast<float*>(smem + OFF_RED_Q);
            float acc[3][4];
#pragma unroll
            for (int mt = 0; mt < 3; mt++) { acc[mt][0] = acc[mt][1] = acc[mt][2] = acc[mt][3] = 0.f; }
#pragma unroll
            for (int i = 0; i < 5; i++) {
                const uint32_t rowaddr = sbase + OFF_WQO + (16 * (5 * hw + i) + krow) * 96 + mhi * 16;
#pragma unroll
                for (int mt = 0; mt < 3; mt++) {
                    uint32_t a[4];
                    ldsm4t(a, rowaddr + mt * 32);
                    mma16816(acc[mt], a, bf[i][0], bf[i][1]);
                }
            }
            if (j == 0) {
#pragma unroll
                for (int mt = 0; mt < 3; mt++) {
                    red[hw * 96 + 16 * mt + g] = acc[mt][0];
                    red[hw * 96 + 48 + 16 * mt + g] = acc[mt][1];
                    red[hw * 96 + 16 * mt + 8 + g] = acc[mt][2];
                    red[hw * 96 + 48 + 16 * mt + 8 + g] = acc[mt][3];
                }
            }
            named_bar(2, NHELP_WARPS * 32);
            if (ht < 96) {
                float s = 0.f;
#pragma unroll
                for (int k = 0; k < 8; k++) s += red[k * 96 + ht];
                red[8 * 96 + ht] = s;
            }
            named_bar(2, NHELP_WARPS * 32);
            if (ht < 16) {
                const int b = ht >> 3, jj = (ht >> 1) & 3, e2 = ht & 1;
                uint32_t fw[3];
#pragma unroll
                for (int r = 0; r < 3; r++) {
                    const int rl = 3 * e2 + r;
                    const int col = 16 * (rl >> 1) + 8 * (rl & 1) + 2 * jj;
                    fw[r] = pack_bf16(red[8 * 96 + b * 48 + col], red[8 * 96 + b * 48 + col + 1]);
                }
                st_ll(g_qll + (b * NH + head) * 32 + jj * 8 + 2 * qd + e2, fw[0], fw[1], fw[2], flag);
            }
            named_bar(2, NHELP_WARPS * 32);
            if (ht == 0) {
                PROF(10);
                mbar_arrive(bar_qdone);
                fence_proxy_async();
                mbar_expect_tx(bar_wo, 61440);
                tma3d_hint(sbase + OFF_WQO, &tmWo, 0, 0, cta * 48, bar_wo, policy_evict_first());
            }
            if (head >= NH - NDIRECT) st_ll(g_y + ((head - (NH - NDIRECT)) * 4 + qd) * 256 + ht, 0u, 0u, 0u, 0u);
            if (head == NH - 1 && ht < NGO) st_ll(g_go + ht * 8 + qd, 0u, 0u, 0u, 0u);
            if (cta < NMLP) {
#pragma unroll
                for (int i = 0; i < 3; i++) if (ht + 256 * i < DM) st_ll(g_z + (size_t)cta * DM + ht + 256 * i, 0u, 0u, 0u, 0u);
            }
            if (cta == 0) {
#pragma unroll
                for (int i = 0; i < 5; i++) g_hacc[(epoch + 1) & 1][ht + 256 * i] = 0.f;
            }
        }

        __nv_bfloat16* obf = reinterpret_cast<__nv_bfloat16*>(smem + OFF_OBF);
        uint32_t wof[3][5][4];
        mbar_wait(bar_wo, 0);
#pragma unroll
        for (int i = 0; i < 5; i++) {
            const int mt = 5 * hw + i;
#pragma unroll
            for (int ks = 0; ks < 3; ks++) {
                const int line = (16 * ks + krow) * 10 + (mt >> 2);
                ldsm4t(wof[ks][i], sbase + OFF_WQO + line * 128 + (((2 * (mt & 3) + mhi) ^ (line & 7)) << 4));
            }
        }
#pragma unroll 1
        for (int b = 0; b < NB; b++) {
            const int bh = b * NH + head;
            const bool last = (bh == NBH - 1), direct = (bh >= NBH - NDIRECT);
            uint4 hd[5], dt[5];
            const uint32_t tag = flag * 8u + (uint32_t)(bh >> 3);
#pragma unroll 1
            for (int pass = last ? 0 : 1; pass < 2; pass++) {
                if (pass) {
                    if (last) mbar_wait(bar_cdone, 0);
                    else {
                        if (ht == 0) wait_claims(min((bh + 1) * TPB + (direct ? 1 : MERGE_MARGIN) * G, NUNITS - G));
                        named_bar(2, NHELP_WARPS * 32);
                    }
                } else {
                    if (ht == 0) wait_claims(NUNITS - G - 400);
                    named_bar(2, NHELP_WARPS * 32);
                }
                const uint32_t pend = pass ? tag - 1u : tag;
#pragma unroll
                for (int s = 0; s < 5; s++) {
                    const uint32_t st = (lane + 32 * s < G) ? pend : tag;
                    hd[s] = make_uint4(0xff800000u, 0u, 0u, st); dt[s] = make_uint4(0u, 0u, 0u, st);
                }
                {
                    const uint4* hp = g_hdr + (bh & (PSLOTS - 1)) * MAXG + lane;
                    const uint4* dp = g_dat + (((bh & (PSLOTS - 1)) * 4 + qd) * 8 + hw) * MAXG + lane;
                    while (true) {
#pragma unroll
                        for (int s = 0; s < 5; s++) {
                            if (dt[s].w != tag) dt[s] = ld_ll(dp + 32 * s);
                            if (hd[s].w != tag) hd[s] = ld_ll(hp + 32 * s);
                        }
                        bool ok = true;
#pragma unroll
                        for (int s = 0; s < 5; s++) ok = ok && dt[s].w == tag && hd[s].w == tag;
                        if (__all_sync(0xffffffffu, ok)) break;
                        if (!last) __nanosleep(direct ? 250 : 500);
                        spin_check(tstart);
                    }
                }
                if (last && pass && ht < NGO) st_ll(g_go + ht * 8 + qd, 0u, 0u, 0u, flag);
                TP(6);
                const float M = warp_max(fmaxf(fmaxf(fmaxf(__uint_as_float(hd[0].x), __uint_as_float(hd[1].x)),
                                               fmaxf(__uint_as_float(hd[2].x), __uint_as_float(hd[3].x))), __uint_as_float(hd[4].x)));
                float a[8];
#pragma unroll
                for (int i = 0; i < 8; i++) a[i] = 0.f;
#pragma unroll
                for (int s = 0; s < 5; s++) {
                    const float wgt = ex2((__uint_as_float(hd[s].x) - M) * LOG2E);
                    a[0] = fmaf(wgt, __uint_as_float(dt[s].x << 16), a[0]);
                    a[1] = fmaf(wgt, __uint_as_float(dt[s].x & 0xffff0000u), a[1]);
                    a[2] = fmaf(wgt, __uint_as_float(dt[s].y << 16), a[2]);
                    a[3] = fmaf(wgt, __uint_as_float(dt[s].y & 0xffff0000u), a[3]);
                    a[4] = fmaf(wgt, __uint_as_float(dt[s].z << 16), a[4]);
                    a[5] = fmaf(wgt, __uint_as_float(dt[s].z & 0xffff0000u), a[5]);
                    a[6] = fmaf(wgt, __uint_as_float(hd[s].y), a[6]);
                }
                {
                    const bool up16 = lane & 16, up8 = lane & 8, up4 = lane & 4;
#pragma unroll
                    for (int i = 0; i < 4; i++) a[i] = (up16 ? a[i + 4] : a[i]) + __shfl_xor_sync(0xffffffffu, up16 ? a[i] : a[i + 4], 16);
#pragma unroll
                    for (int i = 0; i < 2; i++) a[i] = (up8 ? a[i + 2] : a[i]) + __shfl_xor_sync(0xffffffffu, up8 ? a[i] : a[i + 2], 8);
                    a[0] = (up4 ? a[1] : a[0]) + __shfl_xor_sync(0xffffffffu, up4 ? a[0] : a[1], 4);
                    a[0] += __shfl_xor_sync(0xffffffffu, a[0], 2);
                    a[0] += __shfl_xor_sync(0xffffffffu, a[0], 1);
                    const float Lt = __shfl_sync(0xffffffffu, a[0], 24);
                    if (g < 6 && j == 0) obf[8 * g + hw] = __float2bfloat16(a[0] * rcp_fast(Lt));
                }
                named_bar(2, NHELP_WARPS * 32);
                TP(7);
                float yv[10];
                {
                    const uint32_t* ow = reinterpret_cast<const uint32_t*>(obf);
                    uint32_t bq[3][2];
#pragma unroll
                    for (int ks = 0; ks < 3; ks++) { bq[ks][0] = ow[8 * ks + j]; bq[ks][1] = ow[8 * ks + 4 + j]; }
                    float acc[5][4];
#pragma unroll
                    for (int i = 0; i < 5; i++) acc[i][0] = acc[i][1] = acc[i][2] = acc[i][3] = 0.f;
#pragma unroll
                    for (int ks = 0; ks < 3; ks++) {
#pragma unroll
                        for (int i = 0; i < 5; i++) mma16816(acc[i], wof[ks][i], bq[ks][0], bq[ks][1]);
                    }
#pragma unroll
                    for (int i = 0; i < 5; i++) { yv[2 * i] = acc[i][0]; yv[2 * i + 1] = acc[i][2]; }
                }
                const float y0 = j == 0 ? yv[0] : (j == 1 ? yv[3] : (j == 2 ? yv[6] : yv[9]));
                const float y1 = j == 0 ? yv[1] : (j == 1 ? yv[4] : yv[7]);
                const float y2 = j == 0 ? yv[2] : (j == 1 ? yv[5] : yv[8]);
                if (pass) {
                    if (direct) {
                        st_ll(g_y + ((bh - (NBH - NDIRECT)) * 4 + qd) * 256 + ht, __float_as_uint(y0), __float_as_uint(y1), __float_as_uint(y2), flag);
                    } else {
                        red_add_f32(hacc + b * DM + own[0], y0);
                        if (j < 3) { red_add_f32(hacc + b * DM + own[1], y1); red_add_f32(hacc + b * DM + own[2], y2); }
                    }
                }
                TP(8);
                named_bar(2, NHELP_WARPS * 32);
            }
            if (ht == 0) {
                fence_gpu();
                if (!direct) red_add_u32(&g_ycnt.v, 1u);
                asm volatile("st.relaxed.gpu.global.u32 [%0], %1;" :: "l"(reinterpret_cast<unsigned*>(g_done + bh) + qd), "r"(flag) : "memory");
            }
        }
        if (ht == 0) { TPOUT(11, 6); TPOUT(12, 7); TPOUT(4, 8); }
        if (cta >= NMLP) return;

        float hpre[3] = {0.f, 0.f, 0.f}, shift1 = 0.f;
        __nv_bfloat16* hn = reinterpret_cast<__nv_bfloat16*>(smem + OFF_HROW);
        const uint32_t* hnw = reinterpret_cast<const uint32_t*>(hn + (g & 1) * DM + 80 * hw) + j;
        float* red1 = reinterpret_cast<float*>(smem + OFF_RED1);
        uint4* const zout = g_z + (size_t)cta * DM + 80 * hw + g;
#pragma unroll 1
        for (int pass = 0; pass < 2; pass++) {
            if (pass) {
                if (ht == 0) { wait_claims((NBH - NDIRECT) * TPB - G); wait_counter(&g_ycnt.v, flag * YCNT, 200); }
                named_bar(2, NHELP_WARPS * 32);
                float h0[3];
#pragma unroll
                for (int t = 0; t < 3; t++) {
                    h0[t] = rbf(xv[0][t] + rbf(ld_relaxed_f32(hacc + own[t])));
                    hpre[t] = ld_relaxed_f32(hacc + DM + own[t]);
                }
                ln_row(h0, row_mean(h0, reinterpret_cast<float*>(stats + 16), hw, lane), hn, stats, hw, lane);
                TP(9);
#pragma unroll 1
                for (int dd = 0; dd < NDIRECT - 2; dd++) {
                    if (ht < 4) {
                        const uint4* yp = g_y + (dd * 4 + ht) * 256;
                        while (ld_ll(yp).w != flag) { __nanosleep(64); spin_check(tstart); }
                    }
                    named_bar(2, NHELP_WARPS * 32);
                    uint4 y[4];
                    const uint4* yp = g_y + dd * 1024 + ht;
#pragma unroll
                    for (int s = 0; s < 4; s++) y[s] = ld_ll(yp + s * 256);
#pragma unroll
                    for (int s = 0; s < 4; s++) {
                        while (y[s].w != flag) { y[s] = ld_ll(yp + s * 256); spin_check(tstart); }
                        hpre[0] += __uint_as_float(y[s].x); hpre[1] += __uint_as_float(y[s].y); hpre[2] += __uint_as_float(y[s].z);
                    }
                }
                {
                    const float hp1[3] = {xv[1][0] + hpre[0], xv[1][1] + hpre[1], xv[1][2] + hpre[2]};
                    named_bar(2, NHELP_WARPS * 32);
                    shift1 = row_mean(hp1, reinterpret_cast<float*>(stats + 16), hw, lane);
                }
                TP(10);
            }
            uint32_t w1f[5][4], w2f[5][4];
            if (pass) mbar_wait(bar_w1, 0);
#pragma unroll
            for (int i = 0; i < 5; i++) ldsm4t(w1f[i], sbase + OFF_W1 + (16 * (5 * hw + i) + krow) * 32 + mhi * 16);
            if (pass) mbar_wait(bar_w2, 0);
#pragma unroll
            for (int i = 0; i < 5; i++) {
                const int mt = 5 * hw + i, line = krow * 10 + (mt >> 2);
                ldsm4t(w2f[i], sbase + OFF_W2 + line * 128 + (((2 * (mt & 3) + mhi) ^ (line & 7)) << 4));
            }
            if (pass) {
                if (lane < 4) { while (ld_ll(g_go + ((cta + 2 * hw) & (NGO - 1)) * 8 + lane).w != flag) spin_check(tstart); }
                __syncwarp();
                busy_until(clock64() + YWAIT);
            }
            TP(0);
            uint4 y[8];
            const uint4* yp = g_y + (NDIRECT - 2) * 1024 + ht;
#pragma unroll
            for (int s = 0; s < 8; s++) y[s] = make_uint4(0u, 0u, 0u, pass ? flag - 1u : flag);
            while (true) {
                bool ok = true;
#pragma unroll
                for (int s = 0; s < 8; s++) if (y[s].w != flag) y[s] = ld_ll(yp + s * 256);
#pragma unroll
                for (int s = 0; s < 8; s++) ok = ok && y[s].w == flag;
                if (ok) break;
                spin_check(tstart);
            }
            float v[3];
            {
                float a0 = hpre[0], a1 = hpre[1], a2 = hpre[2], b0 = 0.f, b1 = 0.f, b2 = 0.f;
#pragma unroll
                for (int s = 0; s < 4; s++) {
                    a0 += __uint_as_float(y[s].x); a1 += __uint_as_float(y[s].y); a2 += __uint_as_float(y[s].z);
                    b0 += __uint_as_float(y[4 + s].x); b1 += __uint_as_float(y[4 + s].y); b2 += __uint_as_float(y[4 + s].z);
                }
                v[0] = rbf(xv[1][0] + rbf(a0 + b0)); v[1] = rbf(xv[1][1] + rbf(a1 + b1)); v[2] = rbf(xv[1][2] + rbf(a2 + b2));
            }
            TP(1);
            ln_row(v, shift1, hn + DM, stats + 8, hw, lane);
            TP(2);
            float acc0[4] = {0.f, 0.f, 0.f, 0.f}, acc1[4] = {0.f, 0.f, 0.f, 0.f};
#pragma unroll
            for (int i = 0; i < 5; i++) {
                const uint32_t b0 = hnw[8 * i], b1 = hnw[8 * i + 4];
                if (i & 1) mma16816(acc1, w1f[i], b0, b1); else mma16816(acc0, w1f[i], b0, b1);
            }
            if (j == 0) {
                red1[hw * 32 + g] = acc0[0] + acc1[0]; red1[hw * 32 + 16 + g] = acc0[1] + acc1[1];
                red1[hw * 32 + 8 + g] = acc0[2] + acc1[2]; red1[hw * 32 + 16 + 8 + g] = acc0[3] + acc1[3];
            }
            named_bar(2, NHELP_WARPS * 32);
            TP(3);
            uint32_t b0, b1;
            {
                const float* rp = red1 + (g & 1) * 16 + 2 * j;
                float2 p[8], q[8];
#pragma unroll
                for (int k = 0; k < 8; k++) { p[k] = *reinterpret_cast<const float2*>(rp + k * 32); q[k] = *reinterpret_cast<const float2*>(rp + k * 32 + 8); }
                const float lx = ((p[0].x + p[1].x) + (p[2].x + p[3].x)) + ((p[4].x + p[5].x) + (p[6].x + p[7].x));
                const float ly = ((p[0].y + p[1].y) + (p[2].y + p[3].y)) + ((p[4].y + p[5].y) + (p[6].y + p[7].y));
                const float hx = ((q[0].x + q[1].x) + (q[2].x + q[3].x)) + ((q[4].x + q[5].x) + (q[6].x + q[7].x));
                const float hy = ((q[0].y + q[1].y) + (q[2].y + q[3].y)) + ((q[4].y + q[5].y) + (q[6].y + q[7].y));
                b0 = pack_bf16(fmaxf(lx, 0.f), fmaxf(ly, 0.f));
                b1 = pack_bf16(fmaxf(hx, 0.f), fmaxf(hy, 0.f));
            }
            TP(4);
            float z[5][4];
#pragma unroll
            for (int i = 0; i < 5; i++) { z[i][0] = z[i][1] = z[i][2] = z[i][3] = 0.f; mma16816(z[i], w2f[i], b0, b1); }
            {
                const bool j1 = j & 1, j2 = j & 2;
                const float za0 = j2 ? (j1 ? z[1][2] : z[1][0]) : (j1 ? z[0][2] : z[0][0]), zb0 = j2 ? (j1 ? z[1][3] : z[1][1]) : (j1 ? z[0][3] : z[0][1]);
                const float za1 = j2 ? (j1 ? z[3][2] : z[3][0]) : (j1 ? z[2][2] : z[2][0]), zb1 = j2 ? (j1 ? z[3][3] : z[3][1]) : (j1 ? z[2][3] : z[2][1]);
                const float za2 = j1 ? z[4][2] : z[4][0], zb2 = j1 ? z[4][3] : z[4][1];
                if (pass) {
                    st_ll(zout + 8 * j, __float_as_uint(za0), __float_as_uint(zb0), 0u, flag);
                    st_ll(zout + 8 * (4 + j), __float_as_uint(za1), __float_as_uint(zb1), 0u, flag);
                    if (j < 2) st_ll(zout + 8 * (8 + j), __float_as_uint(za2), __float_as_uint(zb2), 0u, flag);
                }
            }
            TP(5);
            if (!pass) named_bar(2, NHELP_WARPS * 32);
        }
        if (ht == 0) { TPOUT(16, 0); TPOUT(17, 1); TPOUT(18, 2); TPOUT(19, 3); TPOUT(20, 4); TPOUT(21, 5); TPOUT(5, 9); TPOUT(6, 10); }
    }
}

typedef CUresult (*EncodeTiledFn)(CUtensorMap*, CUtensorMapDataType, cuuint32_t, void*, const cuuint64_t*, const cuuint64_t*,
                                  const cuuint32_t*, const cuuint32_t*, CUtensorMapInterleave, CUtensorMapSwizzle,
                                  CUtensorMapL2promotion, CUtensorMapFloatOOBfill);

static void make_map_kv(EncodeTiledFn enc, CUtensorMap* tm, const void* base) {
    cuuint64_t dims[2] = {64, (cuuint64_t)NBH * SK * 3};
    cuuint64_t strides[1] = {128};
    cuuint32_t box[2] = {64, 192};
    cuuint32_t es[2] = {1, 1};
    enc(tm, CU_TENSOR_MAP_DATA_TYPE_BFLOAT16, 2, const_cast<void*>(base), dims, strides, box, es,
        CU_TENSOR_MAP_INTERLEAVE_NONE, CU_TENSOR_MAP_SWIZZLE_128B, CU_TENSOR_MAP_L2_PROMOTION_NONE, CU_TENSOR_MAP_FLOAT_OOB_FILL_NONE);
}
static void make_map3(EncodeTiledFn enc, CUtensorMap* tm, const void* base, uint64_t rows, uint32_t box_rows) {
    cuuint64_t dims[3] = {64, 10, rows};
    cuuint64_t strides[2] = {128, DM * 2};
    cuuint32_t box[3] = {64, 10, box_rows};
    cuuint32_t es[3] = {1, 1, 1};
    enc(tm, CU_TENSOR_MAP_DATA_TYPE_BFLOAT16, 3, const_cast<void*>(base), dims, strides, box, es,
        CU_TENSOR_MAP_INTERLEAVE_NONE, CU_TENSOR_MAP_SWIZZLE_128B, CU_TENSOR_MAP_L2_PROMOTION_NONE, CU_TENSOR_MAP_FLOAT_OOB_FILL_NONE);
}

}

extern "C" void kernel_launch(void* const* d_in, const int* in_sizes, int n_in, void* d_out, int out_size) {
    using namespace fused;
    (void)in_sizes; (void)n_in; (void)out_size;
    static EncodeTiledFn enc = nullptr;
    static int grid = 0;
    if (!enc) {
        void* fn = nullptr;
        cudaDriverEntryPointQueryResult qr;
        cudaGetDriverEntryPoint("cuTensorMapEncodeTiled", &fn, cudaEnableDefault, &qr);
        enc = (EncodeTiledFn)fn;
        int dev = 0, sms = 0;
        cudaGetDevice(&dev);
        cudaDeviceGetAttribute(&sms, cudaDevAttrMultiProcessorCount, dev);
        grid = sms < MAXG ? sms : MAXG;
        cudaFuncSetAttribute(fused_decode_kernel, cudaFuncAttributeMaxDynamicSharedMemorySize, SMEM_BYTES);
    }
    CUtensorMap tmK, tmV, tmWo, tmW2;
    make_map_kv(enc, &tmK, d_in[1]);
    make_map_kv(enc, &tmV, d_in[2]);
    make_map3(enc, &tmWo, d_in[4], NH * DH, 48);
    make_map3(enc, &tmW2, d_in[7], DFF, 16);
    fused_decode_kernel<<<grid, NTHREADS, SMEM_BYTES>>>(tmK, tmV, tmWo, tmW2, (const char*)d_in[1], (const char*)d_in[2], (const __nv_bfloat16*)d_in[0], (const __nv_bfloat16*)d_in[3],
                                                        (const __nv_bfloat16*)d_in[6], (const __nv_bfloat16*)d_in[7], (__nv_bfloat16*)d_out);
}
```

```cpp
#include <cuda_runtime.h>
#include <cuda_bf16.h>
#include <cuda.h>
#include <stdint.h>

namespace fused {

constexpr int NB = 2, DM = 640, NH = 32, SK = 16384, DH = 192, DFF = 1536;
constexpr int TILE = 64;
constexpr int TPB = SK / TILE;
constexpr int NBH = NB * NH;
constexpr int NUNITS = NBH * TPB;
constexpr int TILE_BYTES = TILE * DH * 2;
constexpr int NS = 5;
constexpr int NSX = 6;
constexpr int G = 128;
constexpr int NMLP = 96;
constexpr int NFIN = 80;
constexpr int NEARLY = 36;
constexpr int NDIRECT = 4;
constexpr int YCNT = G * NB - 4 * NDIRECT;
constexpr int NGO = 16;
constexpr int PSLOTS = 8;

#define MERGE_MARGIN 3
#define YWAIT 600
#define ZWAIT 3500

constexpr int NCONS_WARPS = 4;
constexpr int NHELP_WARPS = 8;
constexpr int NTHREADS = (NCONS_WARPS + NHELP_WARPS + 1) * 32;

constexpr int OFF_RING = 0;
constexpr int OFF_W1 = OFF_RING + NS * TILE_BYTES;
constexpr int OFF_W2 = OFF_W1 + 20480;
constexpr int OFF_WQO = OFF_W2 + 20480;
constexpr int OFF_MISC = OFF_WQO + 61440;
constexpr int OFF_HROW2 = OFF_RING + NSX * TILE_BYTES;
constexpr int OFF_RED_Q = OFF_HROW2 + 5120;
constexpr int OFF_QRAW = OFF_MISC;
constexpr int OFF_DONE = OFF_QRAW + 2048;
constexpr int OFF_HROW = OFF_DONE + 64;
constexpr int OFF_RED1 = OFF_HROW + 2560;
constexpr int OFF_SBUF = OFF_RED1 + 1024;
constexpr int OFF_STATS = OFF_SBUF + 512;
constexpr int OFF_FRED = OFF_STATS + 192;
constexpr int OFF_OBF = OFF_FRED + 384;
constexpr int OFF_META = OFF_OBF + 128;
constexpr int OFF_EPOCH = OFF_META + 32;
constexpr int OFF_BARS = OFF_EPOCH + 16;
constexpr int NBARS = 2 * NSX + 5;
constexpr int SMEM_BYTES = OFF_BARS + NBARS * 8 + 8;
static_assert(SMEM_BYTES <= 232448, "smem");
static_assert(OFF_RED_Q + 9 * 96 * 4 <= OFF_WQO, "q scratch");
static_assert(OFF_EPOCH % 16 == 0 && OFF_W2 % 1024 == 0 && OFF_WQO % 1024 == 0, "align");

constexpr float SM_SCALE = 0.07216878364870322f;
constexpr float LOG2E = 1.4426950408889634f;
constexpr float LN_EPS = 1e-5f;

struct __align__(128) Counter64 { unsigned long long v; unsigned long long pad[15]; };
struct __align__(128) Counter32 { unsigned v; unsigned pad[31]; };
__device__ Counter64 g_claim;
__device__ Counter32 g_ycnt;
__device__ Counter32 g_epoch;
__device__ __align__(128) uint4 g_qll[NBH * 32];
__device__ __align__(128) uint4 g_hdr[PSLOTS * G];
__device__ __align__(128) uint4 g_done[NBH];
__device__ __align__(128) uint4 g_dat[PSLOTS * 4 * 8 * G];
__device__ __align__(128) float g_hacc[2][NB * DM];
__device__ __align__(128) uint4 g_y[NDIRECT * 4 * 128];
__device__ __align__(128) uint4 g_go[NGO * 8];
__device__ __align__(128) uint4 g_z[NMLP * DM];

__device__ __forceinline__ uint32_t smem_u32(const void* p) { return (uint32_t)__cvta_generic_to_shared(p); }
__device__ __forceinline__ void mbar_init(uint32_t bar, uint32_t cnt) {
    asm volatile("mbarrier.init.shared::cta.b64 [%0], %1;" :: "r"(bar), "r"(cnt) : "memory");
}
__device__ __forceinline__ void mbar_expect_tx(uint32_t bar, uint32_t bytes) {
    asm volatile("mbarrier.arrive.expect_tx.shared::cta.b64 _, [%0], %1;" :: "r"(bar), "r"(bytes) : "memory");
}
__device__ __forceinline__ void mbar_arrive(uint32_t bar) {
    asm volatile("mbarrier.arrive.shared::cta.b64 _, [%0];" :: "r"(bar) : "memory");
}
__device__ __forceinline__ bool mbar_try(uint32_t bar, uint32_t parity) {
    uint32_t ok;
    asm volatile("{\n.reg .pred p;\nmbarrier.try_wait.parity.shared::cta.b64 p, [%1], %2;\nselp.u32 %0, 1, 0, p;\n}"
                 : "=r"(ok) : "r"(bar), "r"(parity) : "memory");
    return ok != 0;
}
constexpr long long SPIN_LIMIT = 4000000000LL;
__device__ __forceinline__ void spin_check(long long t0) { if (clock64() - t0 > SPIN_LIMIT) __trap(); }
__device__ __forceinline__ void busy_until(long long t) { while (clock64() < t) { } }
__device__ __forceinline__ void mbar_wait(uint32_t bar, uint32_t parity) {
    if (mbar_try(bar, parity)) return;
    const long long t0 = clock64();
    while (!mbar_try(bar, parity)) spin_check(t0);
}
__device__ __forceinline__ void tma2d_hint(uint32_t dst, const CUtensorMap* tm, int c0, int c1, uint32_t bar, uint64_t pol) {
    asm volatile("cp.async.bulk.tensor.2d.shared::cluster.global.mbarrier::complete_tx::bytes.L2::cache_hint [%0], [%1, {%3, %4}], [%2], %5;"
                 :: "r"(dst), "l"(tm), "r"(bar), "r"(c0), "r"(c1), "l"(pol) : "memory");
}
__device__ __forceinline__ void tma3d_hint(uint32_t dst, const CUtensorMap* tm, int c0, int c1, int c2, uint32_t bar, uint64_t pol) {
    asm volatile("cp.async.bulk.tensor.3d.shared::cluster.global.mbarrier::complete_tx::bytes.L2::cache_hint [%0], [%1, {%3, %4, %5}], [%2], %6;"
                 :: "r"(dst), "l"(tm), "r"(bar), "r"(c0), "r"(c1), "r"(c2), "l"(pol) : "memory");
}
__device__ __forceinline__ void fence_proxy_async() { asm volatile("fence.proxy.async;" ::: "memory"); }
__device__ __forceinline__ void named_bar(int id, int nthreads) {
    asm volatile("bar.sync %0, %1;" :: "r"(id), "r"(nthreads) : "memory");
}
__device__ __forceinline__ void ldsm4(uint32_t (&r)[4], uint32_t addr) {
    asm volatile("ldmatrix.sync.aligned.m8n8.x4.shared.b16 {%0,%1,%2,%3}, [%4];"
                 : "=r"(r[0]), "=r"(r[1]), "=r"(r[2]), "=r"(r[3]) : "r"(addr) : "memory");
}
__device__ __forceinline__ void ldsm4t(uint32_t (&r)[4], uint32_t addr) {
    asm volatile("ldmatrix.sync.aligned.m8n8.x4.trans.shared.b16 {%0,%1,%2,%3}, [%4];"
                 : "=r"(r[0]), "=r"(r[1]), "=r"(r[2]), "=r"(r[3]) : "r"(addr) : "memory");
}
__device__ __forceinline__ void mma16816(float (&c)[4], const uint32_t (&a)[4], uint32_t b0, uint32_t b1) {
    asm volatile("mma.sync.aligned.m16n8k16.row.col.f32.bf16.bf16.f32 {%0,%1,%2,%3}, {%4,%5,%6,%7}, {%8,%9}, {%0,%1,%2,%3};"
                 : "+f"(c[0]), "+f"(c[1]), "+f"(c[2]), "+f"(c[3])
                 : "r"(a[0]), "r"(a[1]), "r"(a[2]), "r"(a[3]), "r"(b0), "r"(b1));
}
__device__ __forceinline__ uint32_t pack_bf16(float lo, float hi) {
    uint32_t r;
    asm("cvt.rn.bf16x2.f32 %0, %1, %2;" : "=r"(r) : "f"(hi), "f"(lo));
    return r;
}
__device__ __forceinline__ float rbf(float x) { return __uint_as_float(pack_bf16(0.f, x) & 0xffff0000u); }
__device__ __forceinline__ float sqrt_fast(float x) { float y; asm("sqrt.approx.f32 %0, %1;" : "=f"(y) : "f"(x)); return y; }
__device__ __forceinline__ float rcp_fast(float x) { float y; asm("rcp.approx.f32 %0, %1;" : "=f"(y) : "f"(x)); return y; }
__device__ __forceinline__ float ex2(float x) { float y; asm("ex2.approx.ftz.f32 %0, %1;" : "=f"(y) : "f"(x)); return y; }
__device__ __forceinline__ void st_ll(uint4* p, uint32_t a, uint32_t b, uint32_t c, uint32_t d) {
    unsigned long long lo = (unsigned long long)a | ((unsigned long long)b << 32);
    unsigned long long hi = (unsigned long long)c | ((unsigned long long)d << 32);
    asm volatile("{\n.reg .b128 t;\nmov.b128 t, {%1, %2};\nst.relaxed.gpu.global.b128 [%0], t;\n}" :: "l"(p), "l"(lo), "l"(hi) : "memory");
}
__device__ __forceinline__ uint4 ld_ll(const uint4* p) {
    unsigned long long lo, hi;
    asm volatile("{\n.reg .b128 t;\nld.relaxed.gpu.global.b128 t, [%2];\nmov.b128 {%0, %1}, t;\n}" : "=l"(lo), "=l"(hi) : "l"(p) : "memory");
    uint4 r; r.x = (uint32_t)lo; r.y = (uint32_t)(lo >> 32); r.z = (uint32_t)hi; r.w = (uint32_t)(hi >> 32);
    return r;
}
__device__ __forceinline__ unsigned ld_relaxed_u32(const unsigned* p) {
    unsigned v; asm volatile("ld.relaxed.gpu.global.u32 %0, [%1];" : "=r"(v) : "l"(p) : "memory"); return v;
}
__device__ __forceinline__ unsigned long long ld_relaxed_u64(const unsigned long long* p) {
    unsigned long long v; asm volatile("ld.relaxed.gpu.global.u64 %0, [%1];" : "=l"(v) : "l"(p) : "memory"); return v;
}
__device__ __forceinline__ float ld_relaxed_f32(const float* p) {
    float v; asm volatile("ld.relaxed.gpu.global.f32 %0, [%1];" : "=f"(v) : "l"(p) : "memory"); return v;
}
__device__ __forceinline__ void fence_gpu() { asm volatile("fence.acq_rel.gpu;" ::: "memory"); }
__device__ __forceinline__ void red_add_u32(unsigned* p, unsigned v) {
    asm volatile("red.relaxed.gpu.global.add.u32 [%0], %1;" :: "l"(p), "r"(v) : "memory");
}
__device__ __forceinline__ void red_add_f32(float* p, float v) {
    asm volatile("red.relaxed.gpu.global.add.f32 [%0], %1;" :: "l"(p), "f"(v) : "memory");
}
__device__ __forceinline__ void wait_counter(const unsigned* p, unsigned target, unsigned sleep_ns) {
    const long long t0 = clock64();
    while (true) {
        unsigned v;
        asm volatile("ld.acquire.gpu.global.u32 %0, [%1];" : "=r"(v) : "l"(p) : "memory");
        if ((int)(v - target) >= 0) break;
        __nanosleep(sleep_ns); spin_check(t0);
    }
}
__device__ __forceinline__ void cp_async16(uint32_t dst, const void* src) {
    asm volatile("cp.async.cg.shared.global [%0], [%1], 16;" :: "r"(dst), "l"(src) : "memory");
}
__device__ __forceinline__ void cp_async16_hint(uint32_t dst, const void* src, uint64_t pol) {
    asm volatile("cp.async.cg.shared.global.L2::cache_hint [%0], [%1], 16, %2;" :: "r"(dst), "l"(src), "l"(pol) : "memory");
}
__device__ __forceinline__ uint64_t policy_evict_first() {
    uint64_t pol;
    asm volatile("createpolicy.fractional.L2::evict_first.b64 %0, 1.0;" : "=l"(pol));
    return pol;
}
__device__ __forceinline__ void cp_async_commit() { asm volatile("cp.async.commit_group;" ::: "memory"); }
__device__ __forceinline__ void cp_async_wait_all() { asm volatile("cp.async.wait_all;" ::: "memory"); }
__device__ __forceinline__ uint4 lds128(uint32_t addr) {
    uint4 r;
    asm volatile("ld.shared.v4.u32 {%0,%1,%2,%3}, [%4];" : "=r"(r.x), "=r"(r.y), "=r"(r.z), "=r"(r.w) : "r"(addr) : "memory");
    return r;
}
__device__ __forceinline__ void sts128(uint32_t addr, uint4 v) {
    asm volatile("st.shared.v4.u32 [%0], {%1,%2,%3,%4};" :: "r"(addr), "r"(v.x), "r"(v.y), "r"(v.z), "r"(v.w) : "memory");
}
__device__ __forceinline__ void y_unpack(const uint4& w, bool odd, float& a, float& b, float& c) {
    a = __uint_as_float(odd ? (w.y & 0xffff0000u) : (w.x << 16));
    b = __uint_as_float(odd ? (w.z << 16) : (w.x & 0xffff0000u));
    c = __uint_as_float(odd ? (w.z & 0xffff0000u) : (w.y << 16));
}
__device__ __forceinline__ float warp_max(float v) {
    int i = __float_as_int(v);
    i ^= (i >> 31) & 0x7fffffff;
    i = __reduce_max_sync(0xffffffffu, i);
    i ^= (i >> 31) & 0x7fffffff;
    return __int_as_float(i);
}

__device__ __forceinline__ void ln_row(const float (&v)[3], float c, __nv_bfloat16* hn, float2* stats, int hw, int lane) {
    const int g = lane >> 2, j = lane & 3;
    const bool full = j < 3;
    const float d0 = v[0] - c, d1 = full ? v[1] - c : 0.f, d2 = full ? v[2] - c : 0.f;
    float s1 = (d0 + d1) + d2, s2 = fmaf(d0, d0, fmaf(d1, d1, d2 * d2));
#pragma unroll
    for (int o = 16; o >= 1; o >>= 1) { s1 += __shfl_xor_sync(0xffffffffu, s1, o); s2 += __shfl_xor_sync(0xffffffffu, s2, o); }
    if (lane == 0) stats[hw] = make_float2(s1, s2);
    named_bar(2, NHELP_WARPS * 32);
    const float4* sp = reinterpret_cast<const float4*>(stats);
    const float4 a = sp[0], b = sp[1], cc = sp[2], d = sp[3];
    const float S1 = (((a.x + a.z) + (b.x + b.z)) + ((cc.x + cc.z) + (d.x + d.z))) * (1.0f / DM);
    const float S2 = (((a.y + a.w) + (b.y + b.w)) + ((cc.y + cc.w) + (d.y + d.w))) * (1.0f / DM);
    const float mb = rbf(c + S1);
    const float rinv = rcp_fast(rbf(sqrt_fast(rbf(rbf(fmaxf(fmaf(-S1, S1, S2), 0.f)) + LN_EPS))));
    __nv_bfloat16* hp = hn + 80 * hw + 24 * j + g;
    hp[0] = __float2bfloat16(rbf(v[0] - mb) * rinv);
    if (full) { hp[8] = __float2bfloat16(rbf(v[1] - mb) * rinv); hp[16] = __float2bfloat16(rbf(v[2] - mb) * rinv); }
    __syncwarp();
}
__device__ __forceinline__ float row_mean(const float (&v)[3], float* st8, int hw, int lane) {
    const bool full = (lane & 3) < 3;
    float s1 = v[0] + (full ? v[1] + v[2] : 0.f);
#pragma unroll
    for (int o = 16; o >= 1; o >>= 1) s1 += __shfl_xor_sync(0xffffffffu, s1, o);
    if (lane == 0) st8[hw] = s1;
    named_bar(2, NHELP_WARPS * 32);
    const float4 a = *reinterpret_cast<const float4*>(st8), b = *reinterpret_cast<const float4*>(st8 + 4);
    return (((a.x + a.y) + (a.z + a.w)) + ((b.x + b.y) + (b.z + b.w))) * (1.0f / DM);
}

__device__ __forceinline__ void ln_rows2(const float (&v)[2][3], float* hrow2, float4* stats, int hw, int lane, uint32_t (&fr)[5][2]) {
    const int g = lane >> 2, j = lane & 3;
    const bool full = j < 3;
    float* hp = hrow2 + 80 * hw + 24 * j + g;
    hp[0] = v[0][0]; hp[DM] = v[1][0];
    if (full) { hp[8] = v[0][1]; hp[16] = v[0][2]; hp[DM + 8] = v[1][1]; hp[DM + 16] = v[1][2]; }
    float c[2], s1[2], s2[2];
#pragma unroll
    for (int r = 0; r < 2; r++) {
        c[r] = __shfl_sync(0xffffffffu, v[r][0], 0);
        const float d0 = v[r][0] - c[r], d1 = full ? v[r][1] - c[r] : 0.f, d2 = full ? v[r][2] - c[r] : 0.f;
        s1[r] = d0 + d1 + d2; s2[r] = d0 * d0 + d1 * d1 + d2 * d2;
    }
#pragma unroll
    for (int o = 16; o >= 1; o >>= 1) {
#pragma unroll
        for (int r = 0; r < 2; r++) { s1[r] += __shfl_xor_sync(0xffffffffu, s1[r], o); s2[r] += __shfl_xor_sync(0xffffffffu, s2[r], o); }
    }
    if (lane == 0) stats[hw] = make_float4(c[0] + s1[0] * (1.0f / 80.0f), s2[0] - s1[0] * s1[0] * (1.0f / 80.0f),
                                           c[1] + s1[1] * (1.0f / 80.0f), s2[1] - s1[1] * s1[1] * (1.0f / 80.0f));
    named_bar(2, NHELP_WARPS * 32);
    const int row = g & 1;
    const float2* sp = reinterpret_cast<const float2*>(stats) + row;
    float mw[8], m2 = 0.f, mean = 0.f;
#pragma unroll
    for (int k = 0; k < 8; k++) { const float2 t = sp[2 * k]; mw[k] = t.x; mean += t.x; m2 += t.y; }
    mean *= 0.125f;
    float dev = 0.f;
#pragma unroll
    for (int k = 0; k < 8; k++) dev += (mw[k] - mean) * (mw[k] - mean);
    const float mb = rbf(mean);
    const float rinv = rcp_fast(rbf(sqrt_fast(rbf(rbf(fmaxf(m2 + 80.0f * dev, 0.f) * (1.0f / DM)) + LN_EPS))));
    const float* fp = hrow2 + row * DM + 80 * hw + 2 * j;
#pragma unroll
    for (int i = 0; i < 5; i++) {
        const float2 p = *reinterpret_cast<const float2*>(fp + 16 * i);
        const float2 q = *reinterpret_cast<const float2*>(fp + 16 * i + 8);
        fr[i][0] = (g < 2) ? pack_bf16(rbf(p.x - mb) * rinv, rbf(p.y - mb) * rinv) : 0u;
        fr[i][1] = (g < 2) ? pack_bf16(rbf(q.x - mb) * rinv, rbf(q.y - mb) * rinv) : 0u;
    }
}

__global__ void __launch_bounds__(NTHREADS, 1)
fused_decode_kernel(const __grid_constant__ CUtensorMap tmK, const __grid_constant__ CUtensorMap tmV,
                    const __grid_constant__ CUtensorMap tmWo, const __grid_constant__ CUtensorMap tmW2,
                    const char* __restrict__ kc, const char* __restrict__ vc,
                    const __nv_bfloat16* __restrict__ x, const __nv_bfloat16* __restrict__ wq,
                    const __nv_bfloat16* __restrict__ w1, const __nv_bfloat16* __restrict__ w2, __nv_bfloat16* __restrict__ out)
{
    extern __shared__ __align__(1024) unsigned char smem[];
    const uint32_t sbase = smem_u32(smem);
    const int tid = threadIdx.x, warp = tid >> 5, lane = tid & 31;
    const int cta = blockIdx.x;

    const uint32_t bar_full = sbase + OFF_BARS;
    const uint32_t bar_empty = bar_full + NSX * 8;
    const uint32_t bar_wo = bar_empty + NSX * 8;
    const uint32_t bar_w1 = bar_wo + 8;
    const uint32_t bar_w2 = bar_w1 + 8;
    const uint32_t bar_cdone = bar_w2 + 8;
    const uint32_t bar_qdone = bar_cdone + 8;
    volatile int* meta = reinterpret_cast<volatile int*>(smem + OFF_META);

    uint64_t pol = 0;
    const long long tstart = clock64();
    if (tid == NTHREADS - 32) {
        pol = policy_evict_first();
        asm volatile("cp.async.bulk.prefetch.L2.global.L2::cache_hint [%0], %1, %2;" :: "l"(kc + (size_t)cta * TILE_BYTES), "r"(TILE_BYTES), "l"(pol) : "memory");
        asm volatile("cp.async.bulk.prefetch.L2.global.L2::cache_hint [%0], %1, %2;" :: "l"(vc + (size_t)cta * TILE_BYTES), "r"(TILE_BYTES), "l"(pol) : "memory");
    }
    const int ht = tid - NCONS_WARPS * 32;
    auto load_wq = [&]() {
        const __nv_bfloat16* src = wq + cta * 48;
        const uint64_t wpol = policy_evict_first();
#pragma unroll
        for (int i = 0; i < 15; i++) {
            const int idx = ht + 256 * i, row = idx / 6, u = idx - 6 * row;
            cp_async16_hint(sbase + OFF_WQO + idx * 16, src + (size_t)row * (NH * DH) + u * 8, wpol);
        }
        cp_async_commit();
    };
    if (warp >= NCONS_WARPS && warp < NCONS_WARPS + NHELP_WARPS) {
        if (ht < 160) cp_async16(sbase + OFF_HROW + ht * 16, x + ht * 8);
        if (ht == 160) cp_async16(sbase + OFF_EPOCH, &g_epoch);
        cp_async_commit();
        if (cta < NEARLY) load_wq();
    }
    if (warp == NCONS_WARPS + NHELP_WARPS && lane == 0) {
        for (int i = 0; i < NSX; i++) { mbar_init(bar_full + 8 * i, 1); mbar_init(bar_empty + 8 * i, NCONS_WARPS); }
        mbar_init(bar_wo, 1); mbar_init(bar_w1, 32); mbar_init(bar_w2, 1); mbar_init(bar_cdone, NCONS_WARPS); mbar_init(bar_qdone, 1);
        asm volatile("fence.mbarrier_init.release.cluster;" ::: "memory");
        asm volatile("fence.proxy.async.shared::cta;" ::: "memory");
        meta[0] = cta;
        mbar_expect_tx(bar_full, TILE_BYTES);
        tma2d_hint(sbase + OFF_RING, &tmK, 0, cta * 192, bar_full, pol);
        mbar_expect_tx(bar_full + 8, TILE_BYTES);
        tma2d_hint(sbase + OFF_RING + TILE_BYTES, &tmV, 0, cta * 192, bar_full + 8, pol);
    }
    __syncthreads();

    if (warp == NCONS_WARPS + NHELP_WARPS) {
        asm volatile("setmaxnreg.dec.sync.aligned.u32 40;");
        if (lane == 0) {
            unsigned long long old = atomicAdd(&g_claim.v, 1ULL);
            int slot = 2, lim = NSX; uint32_t ph = 1;
            int wslot = 0, wlim = NSX; uint32_t wph = 0;
            while (true) {
                const int unit = (int)(old & (NUNITS - 1)) + G;
                if (unit >= NUNITS) break;
                mbar_wait(bar_full + 8 * wslot, wph); if (++wslot == wlim) { wslot = 0; wph ^= 1; wlim = NS; }
                mbar_wait(bar_empty + 8 * slot, ph);
                meta[slot] = unit;
                mbar_expect_tx(bar_full + 8 * slot, TILE_BYTES);
                tma2d_hint(sbase + OFF_RING + slot * TILE_BYTES, &tmK, 0, unit * 192, bar_full + 8 * slot, pol);
                if (++slot == lim) { slot = 0; ph ^= 1; lim = NS; }
                mbar_wait(bar_full + 8 * wslot, wph); if (++wslot == wlim) { wslot = 0; wph ^= 1; wlim = NS; }
                mbar_wait(bar_empty + 8 * slot, ph);
                mbar_expect_tx(bar_full + 8 * slot, TILE_BYTES);
                tma2d_hint(sbase + OFF_RING + slot * TILE_BYTES, &tmV, 0, unit * 192, bar_full + 8 * slot, pol);
                if (++slot == lim) { slot = 0; ph ^= 1; lim = NS; }
                old = atomicAdd(&g_claim.v, 1ULL);
            }
            mbar_wait(bar_empty + 8 * slot, ph);
            meta[slot] = -1;
            mbar_arrive(bar_full + 8 * slot);
        }
        __syncwarp();
        if (cta < NMLP) {
            const __nv_bfloat16* src = w1 + cta * 16;
            const uint64_t wpol = policy_evict_first();
#pragma unroll 4
            for (int i = 0; i < 40; i++) {
                const int idx = lane + 32 * i;
                cp_async16_hint(sbase + OFF_W1 + idx * 16, src + (size_t)(idx >> 1) * DFF + (idx & 1) * 8, wpol);
            }
            asm volatile("cp.async.mbarrier.arrive.noinc.shared::cta.b64 [%0];" :: "r"(bar_w1) : "memory");
            if (lane == 0) {
                mbar_wait(bar_qdone, 0);
                fence_proxy_async();
                mbar_expect_tx(bar_w2, 20480);
                tma3d_hint(sbase + OFF_W2, &tmW2, 0, 0, cta * 16, bar_w2, pol);
            }
            cp_async_wait_all();
        }
    } else if (warp < NCONS_WARPS) {
        asm volatile("setmaxnreg.dec.sync.aligned.u32 96;");
        const int w = warp, g = lane >> 2, j = lane & 3;
        uint4* const dat_base = g_dat + ((size_t)w * 8 + g) * G + cta;
        uint4* const hdr_base = g_hdr + cta;
        const uint32_t epoch = ld_relaxed_u32(&g_epoch.v);
        const uint32_t flag = epoch + 1u;
        uint32_t koff[3];
        {
            const int key = 16 * w + (lane & 7) + 8 * ((lane >> 3) & 1), hi = lane >> 4;
#pragma unroll
            for (int c = 0; c < 3; c++) { const int r = key * 3 + c; koff[c] = r * 128 + (((r & 7) ^ hi) << 4); }
        }
        uint32_t voff[3];
        {
            const int key = (lane & 7) + 8 * (lane >> 4), hi = (lane >> 3) & 1;
#pragma unroll
            for (int mt = 0; mt < 3; mt++) {
                const int U = 6 * w + 2 * mt + hi, c = U >> 3, u = U & 7, r = key * 3 + c;
                voff[mt] = r * 128 + ((u ^ (r & 7)) << 4);
            }
        }
        const bool act = (g >> 1) == j;
        const uint32_t sel0 = act ? ((g & 1) ? 0x1044u : 0x4410u) : 0x4444u;
        const uint32_t sel1 = act ? ((g & 1) ? 0x3244u : 0x4432u) : 0x4444u;
        float* sbuf = reinterpret_cast<float*>(smem + OFF_SBUF);
        const uint32_t qraw = sbase + OFF_QRAW + w * 512;
        const uint32_t dnraw = sbase + OFF_DONE + w * 16;

        uint32_t qf[24];
        float o[3][4];
        float m_run = -INFINITY, l_run = 0.f;
        int cur_bh = -1, pre_bh = -1, done_bh = -1, par = 0;
        int slot = 0, lim = NSX; uint32_t ph = 0;

        auto advance_to = [&](int nb) {
#pragma unroll 1
            while (cur_bh < nb) {
                if (cur_bh >= 0) {
                    if (cur_bh >= PSLOTS) {
                        uint4 dn = lds128(dnraw);
                        if (done_bh != cur_bh - PSLOTS || dn.x != flag || dn.y != flag || dn.z != flag || dn.w != flag) {
                            const long long t0 = clock64();
                            do { dn = ld_ll(g_done + cur_bh - PSLOTS); spin_check(t0); } while (dn.x != flag || dn.y != flag || dn.z != flag || dn.w != flag);
                        }
                    }
                    const uint32_t tag = flag * 8u + (uint32_t)(cur_bh >> 3);
                    float lo[3], hi[3];
#pragma unroll
                    for (int mt = 0; mt < 3; mt++) {
                        lo[mt] = o[mt][0] + o[mt][1]; hi[mt] = o[mt][2] + o[mt][3];
                        lo[mt] += __shfl_xor_sync(0xffffffffu, lo[mt], 1); hi[mt] += __shfl_xor_sync(0xffffffffu, hi[mt], 1);
                        lo[mt] += __shfl_xor_sync(0xffffffffu, lo[mt], 2); hi[mt] += __shfl_xor_sync(0xffffffffu, hi[mt], 2);
                    }
                    if (j == 0)
                        st_ll(dat_base + (cur_bh & (PSLOTS - 1)) * (4 * 8 * G), pack_bf16(lo[0], hi[0]), pack_bf16(lo[1], hi[1]), pack_bf16(lo[2], hi[2]), tag);
                    if (w == 0) {
                        float l = l_run;
                        l += __shfl_xor_sync(0xffffffffu, l, 4);
                        l += __shfl_xor_sync(0xffffffffu, l, 8);
                        l += __shfl_xor_sync(0xffffffffu, l, 16);
                        if (lane == 1) st_ll(hdr_base + (cur_bh & (PSLOTS - 1)) * G, __float_as_uint(m_run), __float_as_uint(l), 0u, tag);
                    }
                }
                m_run = -INFINITY; l_run = 0.f;
#pragma unroll
                for (int mt = 0; mt < 3; mt++) { o[mt][0] = o[mt][1] = o[mt][2] = o[mt][3] = 0.f; }
                cur_bh++;
            }
        };

        {
            if (w == 0) {
                const long long t0 = clock64();
                const uint4* qp = g_qll + lane;
                uint4 r0 = ld_ll(qp);
                while (!__all_sync(0xffffffffu, r0.w == flag)) { __nanosleep(200); r0 = ld_ll(qp); spin_check(t0); }
#pragma unroll
                for (int k = 0; k < NCONS_WARPS; k++) sts128(sbase + OFF_QRAW + k * 512 + lane * 16, r0);
            }
            named_bar(1, NCONS_WARPS * 32);
            pre_bh = 0;
        }

        while (true) {
            mbar_wait(bar_full + 8 * slot, ph);
            const int unit = meta[slot];
            if (unit < 0) break;
            const int bh = unit >> 8;
            if (bh != cur_bh) {
                cp_async_wait_all();
                __syncwarp();
                advance_to(bh);
                bool have = false;
                if (pre_bh == bh) {
                    bool ok = true;
#pragma unroll
                    for (int t = 0; t < 8; t++) {
                        const uint4 r = lds128(qraw + (j * 8 + t) * 16);
                        qf[3 * t] = r.x; qf[3 * t + 1] = r.y; qf[3 * t + 2] = r.z;
                        ok = ok && (r.w == flag);
                    }
                    have = __all_sync(0xffffffffu, ok);
                }
                if (!have) {
                    const long long t0 = clock64();
                    const uint4* qp = g_qll + bh * 32 + lane;
                    uint4 r0 = ld_ll(qp);
                    while (!__all_sync(0xffffffffu, r0.w == flag)) { __nanosleep(200); r0 = ld_ll(qp); spin_check(t0); }
                    sts128(qraw + lane * 16, r0);
                    __syncwarp();
#pragma unroll
                    for (int t = 0; t < 8; t++) {
                        const uint4 r = lds128(qraw + (j * 8 + t) * 16);
                        qf[3 * t] = r.x; qf[3 * t + 1] = r.y; qf[3 * t + 2] = r.z;
                    }
                }
                __syncwarp();
                pre_bh = bh + 1;
                if (pre_bh < NBH) cp_async16(qraw + lane * 16, g_qll + pre_bh * 32 + lane);
                done_bh = bh - PSLOTS;
                if (done_bh >= 0 && lane == 0) cp_async16(dnraw, g_done + done_bh);
            }
            float s0[4] = {0.f, 0.f, 0.f, 0.f}, s1[4] = {0.f, 0.f, 0.f, 0.f}, s2[4] = {0.f, 0.f, 0.f, 0.f};
            {
                const uint32_t kb = sbase + OFF_RING + slot * TILE_BYTES;
#pragma unroll
                for (int i = 0; i < 4; i++) {
                    uint32_t a[4], b[4], c[4];
                    ldsm4(a, kb + (koff[0] ^ (i * 32)));
                    ldsm4(b, kb + (koff[1] ^ (i * 32)));
                    ldsm4(c, kb + (koff[2] ^ (i * 32)));
                    mma16816(s0, a, qf[2 * i], qf[2 * i + 1]);
                    mma16816(s1, b, qf[8 + 2 * i], qf[8 + 2 * i + 1]);
                    mma16816(s2, c, qf[16 + 2 * i], qf[16 + 2 * i + 1]);
                }
            }
            const float slo = rbf(rbf(s0[0] + s1[0] + s2[0]) * SM_SCALE), shi = rbf(rbf(s0[2] + s1[2] + s2[2]) * SM_SCALE);
            __syncwarp();
            if (lane == 0) mbar_arrive(bar_empty + 8 * slot);
            if (++slot == lim) { slot = 0; ph ^= 1; lim = NS; }
            float* sb = sbuf + par * 64;
            if (j == 0) { sb[16 * w + g] = slo; sb[16 * w + 8 + g] = shi; }
            par ^= 1;
            named_bar(1, NCONS_WARPS * 32);
            float sv[8];
#pragma unroll
            for (int kk = 0; kk < 4; kk++) { sv[2 * kk] = sb[16 * kk + g]; sv[2 * kk + 1] = sb[16 * kk + 8 + g]; }
            float mx = fmaxf(fmaxf(fmaxf(sv[0], sv[1]), fmaxf(sv[2], sv[3])), fmaxf(fmaxf(sv[4], sv[5]), fmaxf(sv[6], sv[7])));
            mx = warp_max(mx);
            const float m_new = fmaxf(m_run, mx);
            const float mc = m_new * LOG2E;
            const float alpha = ex2(m_run * LOG2E - mc);
            m_run = m_new;
            uint32_t pb[4][2];
            float psum = 0.f;
#pragma unroll
            for (int kk = 0; kk < 4; kk++) {
                const float p0 = ex2(fmaf(sv[2 * kk], LOG2E, -mc));
                const float p1 = ex2(fmaf(sv[2 * kk + 1], LOG2E, -mc));
                psum += p0 + p1;
                const uint32_t pk = pack_bf16(p0, p1);
                pb[kk][0] = __byte_perm(pk, 0u, sel0);
                pb[kk][1] = __byte_perm(pk, 0u, sel1);
            }
            l_run = l_run * alpha + psum;
#pragma unroll
            for (int mt = 0; mt < 3; mt++) { o[mt][0] *= alpha; o[mt][1] *= alpha; o[mt][2] *= alpha; o[mt][3] *= alpha; }
            mbar_wait(bar_full + 8 * slot, ph);
            {
                const uint32_t vb = sbase + OFF_RING + slot * TILE_BYTES;
#pragma unroll
                for (int k2 = 0; k2 < 4; k2 += 2) {
                    uint32_t a[2][3][4];
#pragma unroll
                    for (int kk = 0; kk < 2; kk++)
#pragma unroll
                        for (int mt = 0; mt < 3; mt++) ldsm4t(a[kk][mt], vb + voff[mt] + (k2 + kk) * 6144);
#pragma unroll
                    for (int kk = 0; kk < 2; kk++)
#pragma unroll
                        for (int mt = 0; mt < 3; mt++) mma16816(o[mt], a[kk][mt], pb[k2 + kk][0], pb[k2 + kk][1]);
                }
            }
            __syncwarp();
            if (lane == 0) mbar_arrive(bar_empty + 8 * slot);
            if (++slot == lim) { slot = 0; ph ^= 1; lim = NS; }
        }
        cp_async_wait_all();
        __syncwarp();
        advance_to(NBH);
        if (lane == 0) mbar_arrive(bar_cdone);
        __syncwarp();
        if (cta < NFIN) {
            const int nn = lane & 7, sub = lane >> 3;
            const int n = 8 * cta + nn;
            const long long t0 = clock64();
            float* fred = reinterpret_cast<float*>(smem + OFF_FRED);
            const int hw2 = n / 80, r = n - 80 * hw2, idx = r >> 3, jj = idx >= 6, tt = idx - 6 * jj;
            const int yoff = sub * 128 + hw2 * 16 + nn * 2 + jj;
            const uint4* zp = g_z + (size_t)(24 * w + sub) * DM + n;
            float xb = 0.f, abase = 0.f, yv = 0.f;
            if (lane < 4) { while (ld_ll(g_go + ((cta + 4 * w) & (NGO - 1)) * 8 + lane).w != flag) spin_check(t0); }
            __syncwarp();
            const long long t1 = clock64();
#pragma unroll 1
            for (int pass = 0; pass < 2; pass++) {
                if (pass) {
                    if (w == 0) {
                        if (lane == 0) wait_counter(&g_ycnt.v, flag * YCNT, 100);
                        __syncwarp();
                        if (lane < 16) { xb = __bfloat162float(x[sub * DM + n]); abase = ld_relaxed_f32(g_hacc[epoch & 1] + sub * DM + n); }
                    }
                    if (w < NDIRECT) {
                        if (w == NDIRECT - 1) busy_until(t1 + YWAIT + 300);
                        const uint4* yp = g_y + w * 512 + yoff;
                        uint4 d = ld_ll(yp);
                        while (d.w != flag) { d = ld_ll(yp); spin_check(t0); }
                        const uint32_t wd = tt < 2 ? d.x : (tt < 4 ? d.y : d.z);
                        yv = __uint_as_float((tt & 1) ? (wd & 0xffff0000u) : (wd << 16));
                    }
                    busy_until(t1 + ZWAIT);
                }
                uint4 d[6];
#pragma unroll
                for (int s = 0; s < 6; s++) d[s] = make_uint4(0u, 0u, 0u, pass ? flag - 1u : flag);
                while (true) {
                    bool ok = true;
#pragma unroll
                    for (int s = 0; s < 6; s++) { if (d[s].w != flag) d[s] = ld_ll(zp + (size_t)4 * s * DM); }
#pragma unroll
                    for (int s = 0; s < 6; s++) ok = ok && d[s].w == flag;
                    if (ok) break;
                    spin_check(t0);
                }
                float z0 = 0.f, z1 = 0.f, ya = yv;
#pragma unroll
                for (int s = 0; s < 6; s++) { z0 += __uint_as_float(d[s].x); z1 += __uint_as_float(d[s].y); }
                __syncwarp();
                z0 += __shfl_xor_sync(0xffffffffu, z0, 8); z1 += __shfl_xor_sync(0xffffffffu, z1, 8); ya += __shfl_xor_sync(0xffffffffu, ya, 8);
                z0 += __shfl_xor_sync(0xffffffffu, z0, 16); z1 += __shfl_xor_sync(0xffffffffu, z1, 16); ya += __shfl_xor_sync(0xffffffffu, ya, 16);
                if (lane < 8) { fred[w * 24 + nn] = z0; fred[w * 24 + 8 + nn] = z1; fred[w * 24 + 16 + nn] = ya; }
                named_bar(1, NCONS_WARPS * 32);
                if (w == 0 && lane < 16) {
                    const float mlp = (fred[lane] + fred[24 + lane]) + (fred[48 + lane] + fred[72 + lane]);
                    const float yd = (fred[16 + nn] + fred[40 + nn]) + (fred[64 + nn] + fred[88 + nn]);
                    const float h = rbf(xb + rbf(abase + (sub ? yd : 0.f)));
                    if (pass) out[sub * DM + n] = __float2bfloat16(h + rbf(mlp));
                }
                if (!pass) named_bar(1, NCONS_WARPS * 32);
            }
            if (cta == 0 && w == 0 && lane == 0) g_epoch.v = epoch + 1u;
        }
    } else {
        asm volatile("setmaxnreg.inc.sync.aligned.u32 144;");
        const int hw = warp - NCONS_WARPS;
        const int g = lane >> 2, j = lane & 3;
        const int head = cta >> 2, qd = cta & 3;
        int own[3];
#pragma unroll
        for (int t = 0; t < 3; t++) own[t] = 80 * hw + 8 * ((j < 3) ? 3 * j + t : 9) + g;
        if (ht < 16) st_ll(g_qll + ((ht >> 3) * NH + head) * 32 + ((ht >> 1) & 3) * 8 + 2 * qd + (ht & 1), 0u, 0u, 0u, 0u);
        float xv[2][3];
        {
            if (cta < NEARLY) asm volatile("cp.async.wait_group 1;" ::: "memory"); else asm volatile("cp.async.wait_group 0;" ::: "memory");
            named_bar(2, NHELP_WARPS * 32);
            const __nv_bfloat16* xs = reinterpret_cast<const __nv_bfloat16*>(smem + OFF_HROW);
#pragma unroll
            for (int t = 0; t < 3; t++) { xv[0][t] = __bfloat162float(xs[own[t]]); xv[1][t] = __bfloat162float(xs[DM + own[t]]); }
        }
        const uint32_t epoch = *reinterpret_cast<const uint32_t*>(smem + OFF_EPOCH);
        const uint32_t flag = epoch + 1u;
        float* hacc = g_hacc[epoch & 1];
        float2* stats = reinterpret_cast<float2*>(smem + OFF_STATS);
        const int krow = (lane & 7) + 8 * (lane >> 4), mhi = (lane >> 3) & 1;
        auto wait_claims = [&](int target) {
            while (true) {
                const int rem = target - (int)(long long)(ld_relaxed_u64(&g_claim.v) - ((unsigned long long)epoch << 14));
                if (rem <= 0) break;
                const unsigned ns = rem > 2000 ? 8000u : (unsigned)rem * 4u;
                __nanosleep(ns < 64u ? 64u : ns);
                spin_check(tstart);
            }
        };

        {
            uint32_t bf[5][2];
            ln_rows2(xv, reinterpret_cast<float*>(smem + OFF_HROW2), reinterpret_cast<float4*>(smem + OFF_STATS), hw, lane, bf);
            if (cta >= NEARLY) load_wq();
            cp_async_wait_all();
            named_bar(2, NHELP_WARPS * 32);
            float* red = reinterpret_cast<float*>(smem + OFF_RED_Q);
            float acc[3][4];
#pragma unroll
            for (int mt = 0; mt < 3; mt++) { acc[mt][0] = acc[mt][1] = acc[mt][2] = acc[mt][3] = 0.f; }
#pragma unroll
            for (int i = 0; i < 5; i++) {
                const uint32_t rowaddr = sbase + OFF_WQO + (16 * (5 * hw + i) + krow) * 96 + mhi * 16;
#pragma unroll
                for (int mt = 0; mt < 3; mt++) {
                    uint32_t a[4];
                    ldsm4t(a, rowaddr + mt * 32);
                    mma16816(acc[mt], a, bf[i][0], bf[i][1]);
                }
            }
            if (j == 0) {
#pragma unroll
                for (int mt = 0; mt < 3; mt++) {
                    red[hw * 96 + 16 * mt + g] = acc[mt][0];
                    red[hw * 96 + 48 + 16 * mt + g] = acc[mt][1];
                    red[hw * 96 + 16 * mt + 8 + g] = acc[mt][2];
                    red[hw * 96 + 48 + 16 * mt + 8 + g] = acc[mt][3];
                }
            }
            named_bar(2, NHELP_WARPS * 32);
            if (ht < 96) {
                float s = 0.f;
#pragma unroll
                for (int k = 0; k < 8; k++) s += red[k * 96 + ht];
                red[8 * 96 + ht] = s;
            }
            named_bar(2, NHELP_WARPS * 32);
            if (ht < 16) {
                const int b = ht >> 3, jj = (ht >> 1) & 3, e2 = ht & 1;
                uint32_t fw[3];
#pragma unroll
                for (int r = 0; r < 3; r++) {
                    const int rl = 3 * e2 + r;
                    const int col = 16 * (rl >> 1) + 8 * (rl & 1) + 2 * jj;
                    fw[r] = pack_bf16(red[8 * 96 + b * 48 + col], red[8 * 96 + b * 48 + col + 1]);
                }
                st_ll(g_qll + (b * NH + head) * 32 + jj * 8 + 2 * qd + e2, fw[0], fw[1], fw[2], flag);
            }
            named_bar(2, NHELP_WARPS * 32);
            if (ht == 0) {
                mbar_arrive(bar_qdone);
                fence_proxy_async();
                mbar_expect_tx(bar_wo, 61440);
                tma3d_hint(sbase + OFF_WQO, &tmWo, 0, 0, cta * 48, bar_wo, policy_evict_first());
            }
            if (head >= NH - NDIRECT && ht < 128) st_ll(g_y + ((head - (NH - NDIRECT)) * 4 + qd) * 128 + ht, 0u, 0u, 0u, 0u);
            if (head == NH - 1 && ht < NGO) st_ll(g_go + ht * 8 + qd, 0u, 0u, 0u, 0u);
            if (cta < NMLP) {
#pragma unroll
                for (int i = 0; i < 3; i++) if (ht + 256 * i < DM) st_ll(g_z + (size_t)cta * DM + ht + 256 * i, 0u, 0u, 0u, 0u);
            }
            if (cta == 0) {
#pragma unroll
                for (int i = 0; i < 5; i++) g_hacc[(epoch + 1) & 1][ht + 256 * i] = 0.f;
            }
        }

        __nv_bfloat16* obf = reinterpret_cast<__nv_bfloat16*>(smem + OFF_OBF);
        uint32_t wof[3][5][4];
        mbar_wait(bar_wo, 0);
#pragma unroll
        for (int i = 0; i < 5; i++) {
            const int mt = 5 * hw + i;
#pragma unroll
            for (int ks = 0; ks < 3; ks++) {
                const int line = (16 * ks + krow) * 10 + (mt >> 2);
                ldsm4t(wof[ks][i], sbase + OFF_WQO + line * 128 + (((2 * (mt & 3) + mhi) ^ (line & 7)) << 4));
            }
        }
#pragma unroll 1
        for (int b = 0; b < NB; b++) {
            const int bh = b * NH + head;
            const bool last = (bh == NBH - 1), direct = (bh >= NBH - NDIRECT);
            uint4 hd[4], dt[4];
            const uint32_t tag = flag * 8u + (uint32_t)(bh >> 3);
#pragma unroll 1
            for (int pass = last ? 0 : 1; pass < 2; pass++) {
                if (pass) {
                    if (last) mbar_wait(bar_cdone, 0);
                    else {
                        if (ht == 0) wait_claims(min((bh + 1) * TPB + (direct ? 1 : MERGE_MARGIN) * G, NUNITS - G));
                        named_bar(2, NHELP_WARPS * 32);
                    }
                } else {
                    if (ht == 0) wait_claims(NUNITS - G - 400);
                    named_bar(2, NHELP_WARPS * 32);
                }
                const uint32_t pend = pass ? tag - 1u : tag;
#pragma unroll
                for (int s = 0; s < 4; s++) { hd[s] = make_uint4(0u, 0u, 0u, pend); dt[s] = make_uint4(0u, 0u, 0u, pend); }
                {
                    const uint4* hp = g_hdr + (bh & (PSLOTS - 1)) * G + lane;
                    const uint4* dp = g_dat + (((bh & (PSLOTS - 1)) * 4 + qd) * 8 + hw) * G + lane;
                    while (true) {
#pragma unroll
                        for (int s = 0; s < 4; s++) {
                            if (dt[s].w != tag) dt[s] = ld_ll(dp + 32 * s);
                            if (hd[s].w != tag) hd[s] = ld_ll(hp + 32 * s);
                        }
                        bool ok = true;
#pragma unroll
                        for (int s = 0; s < 4; s++) ok = ok && dt[s].w == tag && hd[s].w == tag;
                        if (__all_sync(0xffffffffu, ok)) break;
                        if (!last) __nanosleep(direct ? 250 : 500);
                        spin_check(tstart);
                    }
                }
                if (last && pass && ht < NGO) st_ll(g_go + ht * 8 + qd, 0u, 0u, 0u, flag);
                const float M = warp_max(fmaxf(fmaxf(__uint_as_float(hd[0].x), __uint_as_float(hd[1].x)),
                                               fmaxf(__uint_as_float(hd[2].x), __uint_as_float(hd[3].x))));
                float a[8];
#pragma unroll
                for (int i = 0; i < 8; i++) a[i] = 0.f;
#pragma unroll
                for (int s = 0; s < 4; s++) {
                    const float wgt = ex2((__uint_as_float(hd[s].x) - M) * LOG2E);
                    a[0] = fmaf(wgt, __uint_as_float(dt[s].x << 16), a[0]);
                    a[1] = fmaf(wgt, __uint_as_float(dt[s].x & 0xffff0000u), a[1]);
                    a[2] = fmaf(wgt, __uint_as_float(dt[s].y << 16), a[2]);
                    a[3] = fmaf(wgt, __uint_as_float(dt[s].y & 0xffff0000u), a[3]);
                    a[4] = fmaf(wgt, __uint_as_float(dt[s].z << 16), a[4]);
                    a[5] = fmaf(wgt, __uint_as_float(dt[s].z & 0xffff0000u), a[5]);
                    a[6] = fmaf(wgt, __uint_as_float(hd[s].y), a[6]);
                }
                {
                    const bool up16 = lane & 16, up8 = lane & 8, up4 = lane & 4;
#pragma unroll
                    for (int i = 0; i < 4; i++) a[i] = (up16 ? a[i + 4] : a[i]) + __shfl_xor_sync(0xffffffffu, up16 ? a[i] : a[i + 4], 16);
#pragma unroll
                    for (int i = 0; i < 2; i++) a[i] = (up8 ? a[i + 2] : a[i]) + __shfl_xor_sync(0xffffffffu, up8 ? a[i] : a[i + 2], 8);
                    a[0] = (up4 ? a[1] : a[0]) + __shfl_xor_sync(0xffffffffu, up4 ? a[0] : a[1], 4);
                    a[0] += __shfl_xor_sync(0xffffffffu, a[0], 2);
                    a[0] += __shfl_xor_sync(0xffffffffu, a[0], 1);
                    const float Lt = __shfl_sync(0xffffffffu, a[0], 24);
                    if (g < 6 && j == 0) obf[8 * g + hw] = __float2bfloat16(a[0] * rcp_fast(Lt));
                }
                named_bar(2, NHELP_WARPS * 32);
                float yv[10];
                {
                    const uint32_t* ow = reinterpret_cast<const uint32_t*>(obf);
                    uint32_t bq[3][2];
#pragma unroll
                    for (int ks = 0; ks < 3; ks++) { bq[ks][0] = ow[8 * ks + j]; bq[ks][1] = ow[8 * ks + 4 + j]; }
                    float acc[5][4];
#pragma unroll
                    for (int i = 0; i < 5; i++) acc[i][0] = acc[i][1] = acc[i][2] = acc[i][3] = 0.f;
#pragma unroll
                    for (int ks = 0; ks < 3; ks++) {
#pragma unroll
                        for (int i = 0; i < 5; i++) mma16816(acc[i], wof[ks][i], bq[ks][0], bq[ks][1]);
                    }
#pragma unroll
                    for (int i = 0; i < 5; i++) { yv[2 * i] = acc[i][0]; yv[2 * i + 1] = acc[i][2]; }
                }
                if (pass) {
                    if (direct) {
                        if (j < 2) {
                            const uint32_t w0 = j ? pack_bf16(yv[6], yv[7]) : pack_bf16(yv[0], yv[1]);
                            const uint32_t w1_ = j ? pack_bf16(yv[8], yv[9]) : pack_bf16(yv[2], yv[3]);
                            const uint32_t w2_ = j ? 0u : pack_bf16(yv[4], yv[5]);
                            st_ll(g_y + ((bh - (NBH - NDIRECT)) * 4 + qd) * 128 + hw * 16 + g * 2 + j, w0, w1_, w2_, flag);
                        }
                    } else {
                        const float y0 = j == 0 ? yv[0] : (j == 1 ? yv[3] : (j == 2 ? yv[6] : yv[9]));
                        const float y1 = j == 0 ? yv[1] : (j == 1 ? yv[4] : yv[7]);
                        const float y2 = j == 0 ? yv[2] : (j == 1 ? yv[5] : yv[8]);
                        red_add_f32(hacc + b * DM + own[0], y0);
                        if (j < 3) { red_add_f32(hacc + b * DM + own[1], y1); red_add_f32(hacc + b * DM + own[2], y2); }
                    }
                }
                named_bar(2, NHELP_WARPS * 32);
            }
            if (ht == 0) {
                fence_gpu();
                if (!direct) red_add_u32(&g_ycnt.v, 1u);
                asm volatile("st.relaxed.gpu.global.u32 [%0], %1;" :: "l"(reinterpret_cast<unsigned*>(g_done + bh) + qd), "r"(flag) : "memory");
            }
        }
        if (cta >= NMLP) return;

        float hpre[3] = {0.f, 0.f, 0.f}, shift1 = 0.f;
        const int yword = hw * 16 + g * 2 + (j >> 1);
        __nv_bfloat16* hn = reinterpret_cast<__nv_bfloat16*>(smem + OFF_HROW);
        const uint32_t* hnw = reinterpret_cast<const uint32_t*>(hn + (g & 1) * DM + 80 * hw) + j;
        float* red1 = reinterpret_cast<float*>(smem + OFF_RED1);
        uint4* const zout = g_z + (size_t)cta * DM + 80 * hw + g;
#pragma unroll 1
        for (int pass = 0; pass < 2; pass++) {
            if (pass) {
                if (ht == 0) { wait_claims((NBH - NDIRECT) * TPB - G); wait_counter(&g_ycnt.v, flag * YCNT, 200); }
                named_bar(2, NHELP_WARPS * 32);
                float h0[3];
#pragma unroll
                for (int t = 0; t < 3; t++) {
                    h0[t] = rbf(xv[0][t] + rbf(ld_relaxed_f32(hacc + own[t])));
                    hpre[t] = ld_relaxed_f32(hacc + DM + own[t]);
                }
                ln_row(h0, row_mean(h0, reinterpret_cast<float*>(stats + 16), hw, lane), hn, stats, hw, lane);
#pragma unroll 1
                for (int dd = 0; dd < NDIRECT - 2; dd++) {
                    if (ht < 4) {
                        const uint4* yp = g_y + (dd * 4 + ht) * 128;
                        while (ld_ll(yp).w != flag) { __nanosleep(64); spin_check(tstart); }
                    }
                    named_bar(2, NHELP_WARPS * 32);
                    uint4 y[4];
                    const uint4* yp = g_y + dd * 512 + yword;
#pragma unroll
                    for (int s = 0; s < 4; s++) y[s] = ld_ll(yp + s * 128);
#pragma unroll
                    for (int s = 0; s < 4; s++) {
                        while (y[s].w != flag) { y[s] = ld_ll(yp + s * 128); spin_check(tstart); }
                        float a, b2, c;
                        y_unpack(y[s], j & 1, a, b2, c);
                        hpre[0] += a; hpre[1] += b2; hpre[2] += c;
                    }
                }
                {
                    const float hp1[3] = {xv[1][0] + hpre[0], xv[1][1] + hpre[1], xv[1][2] + hpre[2]};
                    named_bar(2, NHELP_WARPS * 32);
                    shift1 = row_mean(hp1, reinterpret_cast<float*>(stats + 16), hw, lane);
                }
            }
            uint32_t w1f[5][4], w2f[5][4];
            if (pass) mbar_wait(bar_w1, 0);
#pragma unroll
            for (int i = 0; i < 5; i++) ldsm4t(w1f[i], sbase + OFF_W1 + (16 * (5 * hw + i) + krow) * 32 + mhi * 16);
            if (pass) mbar_wait(bar_w2, 0);
#pragma unroll
            for (int i = 0; i < 5; i++) {
                const int mt = 5 * hw + i, line = krow * 10 + (mt >> 2);
                ldsm4t(w2f[i], sbase + OFF_W2 + line * 128 + (((2 * (mt & 3) + mhi) ^ (line & 7)) << 4));
            }
            if (pass) {
                if (lane < 4) { while (ld_ll(g_go + ((cta + 2 * hw) & (NGO - 1)) * 8 + lane).w != flag) spin_check(tstart); }
                __syncwarp();
                busy_until(clock64() + YWAIT);
            }
            uint4 y[8];
            const uint4* yp = g_y + (NDIRECT - 2) * 512 + yword;
#pragma unroll
            for (int s = 0; s < 8; s++) y[s] = make_uint4(0u, 0u, 0u, pass ? flag - 1u : flag);
            while (true) {
                bool ok = true;
#pragma unroll
                for (int s = 0; s < 8; s++) if (y[s].w != flag) y[s] = ld_ll(yp + s * 128);
#pragma unroll
                for (int s = 0; s < 8; s++) ok = ok && y[s].w == flag;
                if (ok) break;
                spin_check(tstart);
            }
            float v[3];
            {
                float a0 = hpre[0], a1 = hpre[1], a2 = hpre[2], b0 = 0.f, b1 = 0.f, b2 = 0.f;
#pragma unroll
                for (int s = 0; s < 4; s++) {
                    float p0, p1, p2, q0, q1, q2;
                    y_unpack(y[s], j & 1, p0, p1, p2);
                    y_unpack(y[4 + s], j & 1, q0, q1, q2);
                    a0 += p0; a1 += p1; a2 += p2; b0 += q0; b1 += q1; b2 += q2;
                }
                v[0] = rbf(xv[1][0] + rbf(a0 + b0)); v[1] = rbf(xv[1][1] + rbf(a1 + b1)); v[2] = rbf(xv[1][2] + rbf(a2 + b2));
            }
            ln_row(v, shift1, hn + DM, stats + 8, hw, lane);
            float acc0[4] = {0.f, 0.f, 0.f, 0.f}, acc1[4] = {0.f, 0.f, 0.f, 0.f};
#pragma unroll
            for (int i = 0; i < 5; i++) {
                const uint32_t b0 = hnw[8 * i], b1 = hnw[8 * i + 4];
                if (i & 1) mma16816(acc1, w1f[i], b0, b1); else mma16816(acc0, w1f[i], b0, b1);
            }
            if (j == 0) {
                red1[hw * 32 + g] = acc0[0] + acc1[0]; red1[hw * 32 + 16 + g] = acc0[1] + acc1[1];
                red1[hw * 32 + 8 + g] = acc0[2] + acc1[2]; red1[hw * 32 + 16 + 8 + g] = acc0[3] + acc1[3];
            }
            named_bar(2, NHELP_WARPS * 32);
            uint32_t b0, b1;
            {
                const float* rp = red1 + (g & 1) * 16 + 2 * j;
                float2 p[8], q[8];
#pragma unroll
                for (int k = 0; k < 8; k++) { p[k] = *reinterpret_cast<const float2*>(rp + k * 32); q[k] = *reinterpret_cast<const float2*>(rp + k * 32 + 8); }
                const float lx = ((p[0].x + p[1].x) + (p[2].x + p[3].x)) + ((p[4].x + p[5].x) + (p[6].x + p[7].x));
                const float ly = ((p[0].y + p[1].y) + (p[2].y + p[3].y)) + ((p[4].y + p[5].y) + (p[6].y + p[7].y));
                const float hx = ((q[0].x + q[1].x) + (q[2].x + q[3].x)) + ((q[4].x + q[5].x) + (q[6].x + q[7].x));
                const float hy = ((q[0].y + q[1].y) + (q[2].y + q[3].y)) + ((q[4].y + q[5].y) + (q[6].y + q[7].y));
                b0 = pack_bf16(fmaxf(lx, 0.f), fmaxf(ly, 0.f));
                b1 = pack_bf16(fmaxf(hx, 0.f), fmaxf(hy, 0.f));
            }
            float z[5][4];
#pragma unroll
            for (int i = 0; i < 5; i++) { z[i][0] = z[i][1] = z[i][2] = z[i][3] = 0.f; mma16816(z[i], w2f[i], b0, b1); }
            {
                const bool j1 = j & 1, j2 = j & 2;
                const float za0 = j2 ? (j1 ? z[1][2] : z[1][0]) : (j1 ? z[0][2] : z[0][0]), zb0 = j2 ? (j1 ? z[1][3] : z[1][1]) : (j1 ? z[0][3] : z[0][1]);
                const float za1 = j2 ? (j1 ? z[3][2] : z[3][0]) : (j1 ? z[2][2] : z[2][0]), zb1 = j2 ? (j1 ? z[3][3] : z[3][1]) : (j1 ? z[2][3] : z[2][1]);
                const float za2 = j1 ? z[4][2] : z[4][0], zb2 = j1 ? z[4][3] : z[4][1];
                if (pass) {
                    st_ll(zout + 8 * j, __float_as_uint(za0), __float_as_uint(zb0), 0u, flag);
                    st_ll(zout + 8 * (4 + j), __float_as_uint(za1), __float_as_uint(zb1), 0u, flag);
                    if (j < 2) st_ll(zout + 8 * (8 + j), __float_as_uint(za2), __float_as_uint(zb2), 0u, flag);
                }
            }
            if (!pass) named_bar(2, NHELP_WARPS * 32);
        }
    }
}

typedef CUresult (*EncodeTiledFn)(CUtensorMap*, CUtensorMapDataType, cuuint32_t, void*, const cuuint64_t*, const cuuint64_t*,
                                  const cuuint32_t*, const cuuint32_t*, CUtensorMapInterleave, CUtensorMapSwizzle,
                                  CUtensorMapL2promotion, CUtensorMapFloatOOBfill);

static void make_map_kv(EncodeTiledFn enc, CUtensorMap* tm, const void* base) {
    cuuint64_t dims[2] = {64, (cuuint64_t)NBH * SK * 3};
    cuuint64_t strides[1] = {128};
    cuuint32_t box[2] = {64, 192};
    cuuint32_t es[2] = {1, 1};
    enc(tm, CU_TENSOR_MAP_DATA_TYPE_BFLOAT16, 2, const_cast<void*>(base), dims, strides, box, es,
        CU_TENSOR_MAP_INTERLEAVE_NONE, CU_TENSOR_MAP_SWIZZLE_128B, CU_TENSOR_MAP_L2_PROMOTION_NONE, CU_TENSOR_MAP_FLOAT_OOB_FILL_NONE);
}
static void make_map3(EncodeTiledFn enc, CUtensorMap* tm, const void* base, uint64_t rows, uint32_t box_rows) {
    cuuint64_t dims[3] = {64, 10, rows};
    cuuint64_t strides[2] = {128, DM * 2};
    cuuint32_t box[3] = {64, 10, box_rows};
    cuuint32_t es[3] = {1, 1, 1};
    enc(tm, CU_TENSOR_MAP_DATA_TYPE_BFLOAT16, 3, const_cast<void*>(base), dims, strides, box, es,
        CU_TENSOR_MAP_INTERLEAVE_NONE, CU_TENSOR_MAP_SWIZZLE_128B, CU_TENSOR_MAP_L2_PROMOTION_NONE, CU_TENSOR_MAP_FLOAT_OOB_FILL_NONE);
}

}

extern "C" void kernel_launch(void* const* d_in, const int* in_sizes, int n_in, void* d_out, int out_size) {
    using namespace fused;
    (void)in_sizes; (void)n_in; (void)out_size;
    static EncodeTiledFn enc = nullptr;
    if (!enc) {
        void* fn = nullptr;
        cudaDriverEntryPointQueryResult qr;
        cudaGetDriverEntryPoint("cuTensorMapEncodeTiled", &fn, cudaEnableDefault, &qr);
        enc = (EncodeTiledFn)fn;
        cudaFuncSetAttribute(fused_decode_kernel, cudaFuncAttributeMaxDynamicSharedMemorySize, SMEM_BYTES);
    }
    CUtensorMap tmK, tmV, tmWo, tmW2;
    make_map_kv(enc, &tmK, d_in[1]);
    make_map_kv(enc, &tmV, d_in[2]);
    make_map3(enc, &tmWo, d_in[4], NH * DH, 48);
    make_map3(enc, &tmW2, d_in[7], DFF, 16);
    fused_decode_kernel<<<G, NTHREADS, SMEM_BYTES>>>(tmK, tmV, tmWo, tmW2, (const char*)d_in[1], (const char*)d_in[2], (const __nv_bfloat16*)d_in[0], (const __nv_bfloat16*)d_in[3],
                                                        (const __nv_bfloat16*)d_in[6], (const __nv_bfloat16*)d_in[7], (__nv_bfloat16*)d_out);
}
```
